```python
import torch

def _softmax(x, axis=-1):
    return torch.softmax(x, dim=axis)
def _gelu(x):
    return torch.nn.functional.gelu(x, approximate="tanh")
def _silu(x):
    return torch.nn.functional.silu(x)
def _sigmoid(x):
    return torch.sigmoid(x)
def _layernorm(x, axis=-1, eps=1e-5):
    m = x.mean(dim=axis, keepdim=True)
    v = x.var(dim=axis, keepdim=True, unbiased=False)
    return (x - m) / torch.sqrt(v + eps)
def _scatter_add(tgt, idx, src, axis=0):
    return tgt.clone().index_add_(axis, idx, src)
def _segment_sum(src, seg, n):
    out = torch.zeros((n,) + src.shape[1:], dtype=src.dtype)
    return out.index_add_(0, seg, src)
def _pad(x, pw):
    flat = tuple(v for pair in reversed(pw) for v in pair)
    return torch.nn.functional.pad(x, flat)

kernel_name = 'gated_mix__sliding_block_cached__glu_gated_geglu__decode'

def setup_inputs():

    _w = (lambda a: (lambda t: t.to(torch.bfloat16) if t.is_floating_point() else t)(torch.as_tensor(a)))
    def _A_setup():
        B, Sq, D = 1, 1, 640
        Hq, Hkv, Sk, Dh = 32, 32, 4096, 192
        assert Hq % Hkv == 0, (Hq, Hkv)
        return {
            "x": _w((lambda *s: torch.randn(*s, dtype=torch.bfloat16) * 0.05)(B, Sq, D)),
            "k_cache": _w((lambda *s: torch.randn(*s, dtype=torch.bfloat16) * 6.4)(B, Hkv, Sk, Dh)),
            "v_cache": _w((lambda *s: torch.randn(*s, dtype=torch.bfloat16) * 0.05)(B, Hkv, Sk, Dh)),
            "wq": _w((lambda *s: torch.randn(*s, dtype=torch.bfloat16) * 6.4)(D, Hq * Dh) * (D ** -0.5)),
            "wo": _w((lambda *s: torch.randn(*s, dtype=torch.bfloat16) * 0.05)(Hq * Dh, D) * ((Hq * Dh) ** -0.5)),
        }
    _A_in = _A_setup()

    def _B_setup():
        B, S, Dm, Df = 1, 1, 640, 1536
        return {
            "x": _w((lambda *s: torch.randn(*s, dtype=torch.bfloat16) * 0.05)(B, S, Dm)),
            "w_gate": _w((lambda *s: torch.randn(*s, dtype=torch.bfloat16) * 0.8)(Dm, Df) * (Dm ** -0.5)),
            "w_up": _w((lambda *s: torch.randn(*s, dtype=torch.bfloat16) * 0.8)(Dm, Df) * (Dm ** -0.5)),
            "w_down": _w((lambda *s: torch.randn(*s, dtype=torch.bfloat16) * 0.8)(Df, Dm) * (Df ** -0.5)),
        }
    _B_in = _B_setup()

    return {
        "A_x": _A_in["x"],
        "A_k_cache": _A_in["k_cache"],
        "A_v_cache": _A_in["v_cache"],
        "A_wq": _A_in["wq"],
        "A_wo": _A_in["wo"],
        "B_x": _B_in["x"],
        "B_w_gate": _B_in["w_gate"],
        "B_w_up": _B_in["w_up"],
        "B_w_down": _B_in["w_down"],
        "gate_w": _w((lambda *s: torch.randn(*s, dtype=torch.bfloat16) * 0.05)(640) * 16.0),
    }

def reference(A_x, A_k_cache, A_v_cache, A_wq, A_wo, B_x, B_w_gate, B_w_up, B_w_down, gate_w):
    def _A_ref(x, k_cache, v_cache, wq, wo):
        B, Sq, D = x.shape
        Hq, Dh = 32, 192
        Hkv, Sk = k_cache.shape[1], k_cache.shape[2]
        W = min(4096, max(256, Sk // 4))
        rep = Hq // Hkv
        q = (lambda x, *d: x.permute(*d))((x @ wq).reshape(B, Sq, Hq, Dh), 0, 2, 1, 3)
        k = (lambda x, n, axis: torch.repeat_interleave(x, n, dim=axis))(k_cache[:, :, Sk - W:, :], rep, axis=1)
        v = (lambda x, n, axis: torch.repeat_interleave(x, n, dim=axis))(v_cache[:, :, Sk - W:, :], rep, axis=1)
        scores = torch.einsum("bhqd,bhkd->bhqk", q, k) * (Dh ** -0.5)
        p = _softmax(scores, axis=-1)
        o = torch.einsum("bhqk,bhkd->bhqd", p, v)
        return (lambda x, *d: x.permute(*d))(o, 0, 2, 1, 3).reshape(B, Sq, Hq * Dh) @ wo

    def _B_ref(x, w_gate, w_up, w_down):
        g = torch.einsum("bsd,df->bsf", x, w_gate)
        u = torch.einsum("bsd,df->bsf", x, w_up)
        h = _gelu(g) * u
        return torch.einsum("bsf,fd->bsd", h, w_down)

    x = A_x
    g = _sigmoid((x * gate_w).sum(-1, keepdims=True))
    a = _A_ref(x, A_k_cache, A_v_cache, A_wq, A_wo)
    b = _B_ref(x, B_w_gate, B_w_up, B_w_down)
    return g * a + (1 - g) * b
```

```cpp
#include <cuda_runtime.h>
#include <cuda_bf16.h>
#include <stdint.h>

namespace {

constexpr int D_MODEL = 640;
constexpr int NH = 32;
constexpr int SK = 4096;
constexpr int DH = 192;
constexpr int WIN = 1024;
constexpr int DF = 1536;
constexpr int NCTA = 128;
constexpr int NTHR = 608;
constexpr int KEYS = WIN / 4;
constexpr int ROWB = DH * 2;
#define WINDOW 6
#define FINAL_POLL_LEAD 1
#define GATE_ITERS 5
#define P1DEPTH 4
constexpr int KV_ITEM = 16 * ROWB;
constexpr int NKV = 16;
constexpr int NW4 = 15;
constexpr int KV_BYTES = KEYS * ROWB;
constexpr int WROWB = D_MODEL * 2;
constexpr int W_ITEM = 4 * WROWB;
constexpr int NRED = 80;
constexpr uint32_t SPIN_LIMIT = 1u << 20;

constexpr int SM_K = 0;
constexpr int SM_V = SM_K + KV_BYTES;
constexpr int SM_RED = SM_V + KV_BYTES;
constexpr int SM_Q = SM_RED + 16 * 288 * 4;
constexpr int SM_S = SM_Q + 288 * 4;
constexpr int SM_C = SM_S + 256 * 4;
constexpr int SM_F = SM_C + 64 * 4;
constexpr int SM_G = SM_F + 128 * 4;
constexpr int SM_BAR = SM_G + 16;
constexpr int NITEM = 2 * NKV + NW4;
constexpr int NBAR = NITEM + 4 + 1;
constexpr int SM_TOTAL = SM_BAR + NBAR * 8;

__device__ __align__(128) uint32_t g_x1[NCTA * 4 * 288];
__device__ __align__(128) uint32_t g_x2[NCTA * 4 * 64];
__device__ __align__(128) uint32_t g_x3[NRED * NCTA * 8];

#define STAMP(i) do {} while (0)

__device__ __forceinline__ uint32_t smem_u32(const void* p) { return (uint32_t)__cvta_generic_to_shared(p); }
__device__ __forceinline__ void mbar_init(uint32_t a, uint32_t c) { asm volatile("mbarrier.init.shared::cta.b64 [%0], %1;" ::"r"(a), "r"(c) : "memory"); }
__device__ __forceinline__ void mbar_expect(uint32_t a, uint32_t tx) { asm volatile("mbarrier.arrive.expect_tx.shared::cta.b64 _, [%0], %1;" ::"r"(a), "r"(tx) : "memory"); }
__device__ __forceinline__ void mbar_arrive(uint32_t a) { asm volatile("mbarrier.arrive.shared::cta.b64 _, [%0];" ::"r"(a) : "memory"); }
__device__ __forceinline__ void mbar_wait(uint32_t a) {
    uint32_t ok, n = 0;
    do {
        asm volatile("{.reg .pred p; mbarrier.try_wait.parity.shared::cta.b64 p, [%1], 0; selp.u32 %0, 1, 0, p;}" : "=r"(ok) : "r"(a) : "memory");
    } while (!ok && ++n < SPIN_LIMIT);
}
__device__ __forceinline__ void bulk_g2s(uint32_t dst, const void* src, uint32_t bytes, uint32_t mbar) {
    asm volatile("cp.async.bulk.shared::cluster.global.mbarrier::complete_tx::bytes [%0], [%1], %2, [%3];" ::"r"(dst), "l"(src), "r"(bytes), "r"(mbar) : "memory");
}
__device__ __forceinline__ void bulk_prefetch_l2(const void* src, uint32_t bytes) {
    asm volatile("cp.async.bulk.prefetch.L2.global [%0], %1;" ::"l"(src), "r"(bytes) : "memory");
}
__device__ __forceinline__ uint4 ldg_stream(const void* p) {
    uint4 v;
    asm volatile("ld.global.nc.L1::no_allocate.v4.u32 {%0,%1,%2,%3}, [%4];" : "=r"(v.x), "=r"(v.y), "=r"(v.z), "=r"(v.w) : "l"(p));
    return v;
}
__device__ __forceinline__ uint4 lds128(uint32_t a) {
    uint4 v;
    asm volatile("ld.shared.v4.u32 {%0,%1,%2,%3}, [%4];" : "=r"(v.x), "=r"(v.y), "=r"(v.z), "=r"(v.w) : "r"(a));
    return v;
}
__device__ __forceinline__ void named_bar(int id, int n) { asm volatile("bar.sync %0, %1;" ::"r"(id), "r"(n) : "memory"); }
__device__ __forceinline__ float bf_lo(uint32_t u) { return __uint_as_float(u << 16); }
__device__ __forceinline__ float bf_hi(uint32_t u) { return __uint_as_float(u & 0xffff0000u); }
__device__ __forceinline__ float rbf(float f) { return __bfloat162float(__float2bfloat16_rn(f)); }
__device__ __forceinline__ uint32_t enc(float f) { uint32_t u = __float_as_uint(f); return u == 0u ? 0x80000000u : u; }
__device__ __forceinline__ void st_relaxed(uint32_t* p, uint32_t v) { asm volatile("st.relaxed.gpu.global.u32 [%0], %1;" ::"l"(p), "r"(v) : "memory"); }
__device__ __forceinline__ void st_relaxed2(uint32_t* p, uint32_t a, uint32_t b) { asm volatile("st.relaxed.gpu.global.v2.u32 [%0], {%1,%2};" ::"l"(p), "r"(a), "r"(b) : "memory"); }
__device__ __forceinline__ void st_relaxed4(uint32_t* p, uint32_t a, uint32_t b, uint32_t c, uint32_t d) { asm volatile("st.relaxed.gpu.global.v4.u32 [%0], {%1,%2,%3,%4};" ::"l"(p), "r"(a), "r"(b), "r"(c), "r"(d) : "memory"); }
__device__ __forceinline__ uint32_t ld_relaxed(const uint32_t* p) { uint32_t v; asm volatile("ld.relaxed.gpu.global.u32 %0, [%1];" : "=r"(v) : "l"(p) : "memory"); return v; }
__device__ __forceinline__ uint2 ld_relaxed2(const uint32_t* p) { uint2 v; asm volatile("ld.relaxed.gpu.global.v2.u32 {%0,%1}, [%2];" : "=r"(v.x), "=r"(v.y) : "l"(p) : "memory"); return v; }
__device__ __forceinline__ uint4 ld_relaxed4(const uint32_t* p) { uint4 v; asm volatile("ld.relaxed.gpu.global.v4.u32 {%0,%1,%2,%3}, [%4];" : "=r"(v.x), "=r"(v.y), "=r"(v.z), "=r"(v.w) : "l"(p) : "memory"); return v; }

__device__ __forceinline__ void fma8(float (&acc)[8], const uint4& v, float c) {
    acc[0] = fmaf(bf_lo(v.x), c, acc[0]); acc[1] = fmaf(bf_hi(v.x), c, acc[1]);
    acc[2] = fmaf(bf_lo(v.y), c, acc[2]); acc[3] = fmaf(bf_hi(v.y), c, acc[3]);
    acc[4] = fmaf(bf_lo(v.z), c, acc[4]); acc[5] = fmaf(bf_hi(v.z), c, acc[5]);
    acc[6] = fmaf(bf_lo(v.w), c, acc[6]); acc[7] = fmaf(bf_hi(v.w), c, acc[7]);
}
__device__ __forceinline__ float dot8(const uint4& v, const float* q, float s) {
    s = fmaf(bf_lo(v.x), q[0], s); s = fmaf(bf_hi(v.x), q[1], s);
    s = fmaf(bf_lo(v.y), q[2], s); s = fmaf(bf_hi(v.y), q[3], s);
    s = fmaf(bf_lo(v.z), q[4], s); s = fmaf(bf_hi(v.z), q[5], s);
    s = fmaf(bf_lo(v.w), q[6], s); s = fmaf(bf_hi(v.w), q[7], s);
    return s;
}

__global__ void __launch_bounds__(NTHR, 1)
fused_decode_kernel(const __nv_bfloat16* __restrict__ x, const __nv_bfloat16* __restrict__ kc, const __nv_bfloat16* __restrict__ vc,
                    const __nv_bfloat16* __restrict__ wq, const __nv_bfloat16* __restrict__ wo,
                    const __nv_bfloat16* __restrict__ wg, const __nv_bfloat16* __restrict__ wu, const __nv_bfloat16* __restrict__ wd,
                    const __nv_bfloat16* __restrict__ gate_w, __nv_bfloat16* __restrict__ out, const uint32_t zero) {
    extern __shared__ __align__(1024) unsigned char sm[];
    const int tid = threadIdx.x, lane = tid & 31;
    const int warp = __shfl_sync(0xffffffffu, tid >> 5, 0);
    const int b = blockIdx.x, h = b >> 2, r = b & 3;
    const uint32_t sbase = smem_u32(sm);
    float* s_red = reinterpret_cast<float*>(sm + SM_RED);
    float* s_q = reinterpret_cast<float*>(sm + SM_Q);
    float* s_s = reinterpret_cast<float*>(sm + SM_S);
    float* s_c = reinterpret_cast<float*>(sm + SM_C);
    float* s_f = reinterpret_cast<float*>(sm + SM_F);
    float* s_g = reinterpret_cast<float*>(sm + SM_G);
    const uint32_t bar_k = sbase + SM_BAR, bar_v = bar_k + 8 * NKV, bar_w = bar_v + 8 * NKV, bar_p = bar_w + 8 * NW4, bar_qk = bar_p + 32;

    if (warp == 18) {
        if (lane == 0) STAMP(0);
        for (int i = lane; i < NBAR; i += 32) mbar_init(bar_k + 8 * i, (i >= NITEM && i < NITEM + 4) ? 18 : 1);
        asm volatile("fence.mbarrier_init.release.cluster;" ::: "memory");
        named_bar(5, NTHR);
        {
            float s = 0.f;
#pragma unroll
            for (int i = 0; i < GATE_ITERS; i++) {
                const uint2 gx = __ldg(reinterpret_cast<const uint2*>(x) + i * 32 + lane);
                const uint2 gw = __ldg(reinterpret_cast<const uint2*>(gate_w) + i * 32 + lane);
                s += rbf(bf_lo(gx.x) * bf_lo(gw.x)); s += rbf(bf_hi(gx.x) * bf_hi(gw.x));
                s += rbf(bf_lo(gx.y) * bf_lo(gw.y)); s += rbf(bf_hi(gx.y) * bf_hi(gw.y));
            }
#pragma unroll
            for (int o = 16; o; o >>= 1) s += __shfl_xor_sync(0xffffffffu, s, o);
            if (lane == 0) {
                const float g = rbf(1.f / (1.f + __expf(-rbf(s))));
                s_g[0] = g;
                s_g[1] = rbf(1.f - g);
            }
        }
        __syncwarp();
        asm volatile("bar.arrive 6, %0;" ::"r"(NTHR) : "memory");
        if (lane == 0) {
            const char* kp = reinterpret_cast<const char*>(kc) + ((size_t)h * SK + (SK - WIN) + r * KEYS) * ROWB;
            const char* vp = reinterpret_cast<const char*>(vc) + ((size_t)h * SK + (SK - WIN) + r * KEYS) * ROWB;
            const char* dp = reinterpret_cast<const char*>(wd) + (size_t)b * 12 * WROWB;
            const char* op = reinterpret_cast<const char*>(wo) + (size_t)b * 48 * WROWB;
#pragma unroll 1
            for (int i = 0; i < NITEM; i++) {
                if (i < WINDOW) {
                    const int pb = (i * 4) / WINDOW;
                    mbar_wait(bar_p + 8 * pb);
                } else {
                    mbar_wait(bar_k + 8 * (i - WINDOW));
                }
                const char* src; uint32_t dst, bytes;
                if (i < NKV) { src = kp + i * KV_ITEM; dst = SM_K + i * KV_ITEM; bytes = KV_ITEM; }
                else if (i < 2 * NKV) { src = vp + (i - NKV) * KV_ITEM; dst = SM_V + (i - NKV) * KV_ITEM; bytes = KV_ITEM; }
                else {
                    const int j = i - 2 * NKV;
                    if (j == 0) { mbar_wait(bar_qk); STAMP(8); }
                    src = j < 3 ? dp + j * W_ITEM : op + (j - 3) * W_ITEM; dst = SM_K + j * W_ITEM; bytes = W_ITEM;
                }
                mbar_expect(bar_k + 8 * i, bytes);
                bulk_g2s(sbase + dst, src, bytes, bar_k + 8 * i);
            }
        }
        return;
    }

    {
        const int cu = tid % 36, rg = tid / 36;
        const int row0 = r * 160 + rg * 10;
        const char* p;
        uint32_t stride;
        if (cu < 24) { p = reinterpret_cast<const char*>(wq + h * DH + cu * 8); stride = NH * DH * 2; }
        else if (cu < 30) { p = reinterpret_cast<const char*>(wg + h * 48 + (cu - 24) * 8); stride = DF * 2; }
        else { p = reinterpret_cast<const char*>(wu + h * 48 + (cu - 30) * 8); stride = DF * 2; }
        p += (size_t)row0 * stride;
        uint4 w[P1DEPTH];
#pragma unroll
        for (int i = 0; i < P1DEPTH; i++) w[i] = ldg_stream(p + (size_t)(i * stride));
        uint32_t xv[5];
#pragma unroll
        for (int i = 0; i < 5; i++) xv[i] = __ldg(reinterpret_cast<const uint32_t*>(x + row0) + i);
        named_bar(5, NTHR);
        float acc[8];
#pragma unroll
        for (int j = 0; j < 8; j++) acc[j] = 0.f;
#pragma unroll
        for (int i = 0; i < 10; i++) {
            const uint4 c = w[i % P1DEPTH];
            const uint32_t dep = c.x & zero;
            if (i + P1DEPTH < 10) w[i % P1DEPTH] = ldg_stream(p + (size_t)((i + P1DEPTH) * stride + dep));
            if (i >= 6 && lane == 0) mbar_arrive(bar_p + 8 * (i - 6) + dep);
            fma8(acc, c, (i & 1) ? bf_hi(xv[i >> 1]) : bf_lo(xv[i >> 1]));
        }
        float4* dst = reinterpret_cast<float4*>(s_red + rg * 288 + cu * 8);
        dst[0] = make_float4(acc[0], acc[1], acc[2], acc[3]);
        dst[1] = make_float4(acc[4], acc[5], acc[6], acc[7]);
    }
    named_bar(6, NTHR);
    if (tid == 0) STAMP(1);
    if (warp < 9) {
        float s = 0.f;
#pragma unroll
        for (int g = 0; g < 16; g++) s += s_red[g * 288 + tid];
        const uint32_t e = enc(s);
#pragma unroll
        for (int d = 0; d < 4; d++) st_relaxed(g_x1 + ((size_t)(h * 4 + d) * 4 + r) * 288 + tid, e);
        uint32_t* in = g_x1 + (size_t)b * 4 * 288 + tid;
        uint32_t v0 = 0, v1 = 0, v2 = 0, v3 = 0, n = 0;
        do {
            v0 = ld_relaxed(in); v1 = ld_relaxed(in + 288); v2 = ld_relaxed(in + 576); v3 = ld_relaxed(in + 864);
        } while ((!v0 || !v1 || !v2 || !v3) && ++n < SPIN_LIMIT);
        st_relaxed(in, 0u); st_relaxed(in + 288, 0u); st_relaxed(in + 576, 0u); st_relaxed(in + 864, 0u);
        s_q[tid] = rbf((__uint_as_float(v0) + __uint_as_float(v1)) + (__uint_as_float(v2) + __uint_as_float(v3)));
    }
    named_bar(7, 576);
    if (tid == 0) STAMP(2);

    if (warp == 17 && lane < 12) {
        const float g = s_q[192 + r * 12 + lane], u = s_q[240 + r * 12 + lane];
        const float ge = rbf(0.5f * g * (1.f + tanhf(0.7978845608028654f * (g + 0.044715f * g * g * g))));
        s_c[lane] = s_g[1] * rbf(ge * u);
    }

    if (warp < 16) {
        const int k4 = lane >> 3, u = lane & 7;
        float q[24];
#pragma unroll
        for (int j = 0; j < 3; j++) {
            const float4 a = *reinterpret_cast<const float4*>(s_q + j * 64 + u * 8), c = *reinterpret_cast<const float4*>(s_q + j * 64 + u * 8 + 4);
            q[j * 8 + 0] = a.x; q[j * 8 + 1] = a.y; q[j * 8 + 2] = a.z; q[j * 8 + 3] = a.w;
            q[j * 8 + 4] = c.x; q[j * 8 + 5] = c.y; q[j * 8 + 6] = c.z; q[j * 8 + 7] = c.w;
        }
#pragma unroll 1
        for (int n = 0; n < 4; n++) {
            const int item = n * 4 + (warp >> 2);
            mbar_wait(bar_k + 8 * item);
            const int key = item * 16 + (warp & 3) * 4 + k4;
            const uint32_t a = sbase + SM_K + key * ROWB + u * 16;
            const uint4 v0 = lds128(a), v1 = lds128(a + 128), v2 = lds128(a + 256);
            float s = dot8(v0, q, 0.f), s1 = dot8(v1, q + 8, 0.f), s2 = dot8(v2, q + 16, 0.f);
            s += s1 + s2;
            s += __shfl_xor_sync(0xffffffffu, s, 1);
            s += __shfl_xor_sync(0xffffffffu, s, 2);
            s += __shfl_xor_sync(0xffffffffu, s, 4);
            if (u == 0) s_s[key] = rbf(rbf(s) * 0.07216878364870322f);
        }
        named_bar(1, 512);
        if (tid == 0) { mbar_arrive(bar_qk); STAMP(3); }
    }

    if (warp < 12) {
        float m = -INFINITY;
#pragma unroll
        for (int i = 0; i < 8; i++) m = fmaxf(m, s_s[lane + 32 * i]);
#pragma unroll
        for (int o = 16; o; o >>= 1) m = fmaxf(m, __shfl_xor_sync(0xffffffffu, m, o));
        const int u = tid % 24, kg = tid / 24;
        float acc[8];
#pragma unroll
        for (int j = 0; j < 8; j++) acc[j] = 0.f;
        float l = 0.f;
#pragma unroll 2
        for (int n = 0; n < 16; n++) {
            const int key = kg + 16 * n;
            const float pj = __expf(s_s[key] - m);
            l += pj;
            mbar_wait(bar_v + 8 * n);
            const uint4 v = lds128(sbase + SM_V + key * ROWB + u * 16);
            fma8(acc, v, pj);
        }
        float4* dst = reinterpret_cast<float4*>(s_red + kg * DH + u * 8);
        dst[0] = make_float4(acc[0], acc[1], acc[2], acc[3]);
        dst[1] = make_float4(acc[4], acc[5], acc[6], acc[7]);
        if (u == 0) s_f[64 + kg] = l;
        named_bar(2, 448);
        if (tid == 0) STAMP(4);
        if (warp < 6) {
            float s = 0.f;
#pragma unroll
            for (int g = 0; g < 16; g++) s += s_red[g * DH + tid];
            st_relaxed(g_x2 + ((size_t)(h * 4 + tid / 48) * 4 + r) * 64 + tid % 48, enc(s));
        } else if (warp == 6) {
            float lt = 0.f;
#pragma unroll
            for (int g = 0; g < 16; g++) lt += s_f[64 + g];
            const int w8 = lane & 7;
            st_relaxed(g_x2 + ((size_t)(h * 4 + (lane >> 3)) * 4 + r) * 64 + 48 + w8, w8 == 0 ? enc(m) : (w8 == 1 ? enc(lt) : 0x3f800000u));
        }
    }

    if (warp >= 8) {
        const int cw = warp - 8, rg = lane >> 3, u = lane & 7;
        uint32_t* in2 = g_x2 + (size_t)b * 4 * 64;
        if (warp >= 16) {
            const int i = tid - 512;
            named_bar(2, 448);
            if (i < 48) {
                uint32_t o[4];
                uint2 ml[4];
                uint32_t n = 0;
                bool done;
                do {
                    done = true;
#pragma unroll
                    for (int s = 0; s < 4; s++) {
                        o[s] = ld_relaxed(in2 + s * 64 + i);
                        ml[s] = ld_relaxed2(in2 + s * 64 + 48);
                    }
#pragma unroll
                    for (int s = 0; s < 4; s++) done = done && o[s] && ml[s].x && ml[s].y;
                } while (!done && ++n < SPIN_LIMIT);
                const float M = fmaxf(fmaxf(__uint_as_float(ml[0].x), __uint_as_float(ml[1].x)), fmaxf(__uint_as_float(ml[2].x), __uint_as_float(ml[3].x)));
                float L = 0.f, acc = 0.f;
#pragma unroll
                for (int s = 0; s < 4; s++) {
                    const float w = __expf(__uint_as_float(ml[s].x) - M);
                    L = fmaf(w, __uint_as_float(ml[s].y), L);
                    acc = fmaf(w, __uint_as_float(o[s]), acc);
                }
                s_c[12 + i] = s_g[0] * rbf(acc / L);
            }
        }
        named_bar(3, 320);
        if (tid == 512) STAMP(5);
        if (warp >= 16) {
            st_relaxed4(in2 + (tid - 512) * 4, 0u, 0u, 0u, 0u);
        }
        float acc[8];
#pragma unroll
        for (int j = 0; j < 8; j++) acc[j] = 0.f;
        const uint32_t abase = sbase + SM_K + rg * WROWB + cw * 128 + u * 16;
#pragma unroll 3
        for (int i = 0; i < NW4; i++) {
            const float c = s_c[i * 4 + rg];
            mbar_wait(bar_w + 8 * i);
            fma8(acc, lds128(abase + i * W_ITEM), c);
        }
        if (tid == 512) STAMP(6);
        const bool hi16 = lane & 16, hi8 = lane & 8;
        float t[4];
#pragma unroll
        for (int j = 0; j < 4; j++) {
            const float send = hi16 ? acc[j] : acc[j + 4];
            const float keep = hi16 ? acc[j + 4] : acc[j];
            t[j] = keep + __shfl_xor_sync(0xffffffffu, send, 16);
        }
        float z[2];
#pragma unroll
        for (int j = 0; j < 2; j++) {
            const float send = hi8 ? t[j] : t[j + 2];
            const float keep = hi8 ? t[j + 2] : t[j];
            z[j] = keep + __shfl_xor_sync(0xffffffffu, send, 8);
        }
        st_relaxed2(g_x3 + ((size_t)(cw * 8 + u) * NCTA + b) * 8 + (hi16 ? 4 : 0) + (hi8 ? 2 : 0), enc(z[0]), enc(z[1]));
    } else if (b < NRED) {
        uint32_t* in3 = g_x3 + (size_t)b * NCTA * 8 + tid * 4;
        uint4 v;
        uint32_t n = 0;
        mbar_wait(bar_w + 8 * (NW4 - FINAL_POLL_LEAD));
        while (true) {
            v = ld_relaxed4(in3);
            if ((v.x && v.y && v.z && v.w) || ++n >= SPIN_LIMIT) break;
        }
        st_relaxed4(in3, 0u, 0u, 0u, 0u);
        __syncwarp();
        float a0 = __uint_as_float(v.x), a1 = __uint_as_float(v.y), a2 = __uint_as_float(v.z), a3 = __uint_as_float(v.w);
#pragma unroll
        for (int o = 2; o <= 16; o <<= 1) {
            a0 += __shfl_xor_sync(0xffffffffu, a0, o); a1 += __shfl_xor_sync(0xffffffffu, a1, o);
            a2 += __shfl_xor_sync(0xffffffffu, a2, o); a3 += __shfl_xor_sync(0xffffffffu, a3, o);
        }
        if (lane < 2) *reinterpret_cast<float4*>(s_f + warp * 8 + lane * 4) = make_float4(a0, a1, a2, a3);
        named_bar(4, 256);
        if (tid < 8) {
            float s = 0.f;
#pragma unroll
            for (int w = 0; w < 8; w++) s += s_f[w * 8 + tid];
            out[b * 8 + tid] = __float2bfloat16_rn(s);
        }
        if (tid == 0) STAMP(7);
    }
}

}

extern "C" void kernel_launch(void* const* d_in, const int* in_sizes, int n_in, void* d_out, int out_size) {
    static bool init = false;
    if (!init) {
        cudaFuncSetAttribute(fused_decode_kernel, cudaFuncAttributeMaxDynamicSharedMemorySize, SM_TOTAL);
        init = true;
    }
    fused_decode_kernel<<<NCTA, NTHR, SM_TOTAL>>>(
        (const __nv_bfloat16*)d_in[0], (const __nv_bfloat16*)d_in[1], (const __nv_bfloat16*)d_in[2], (const __nv_bfloat16*)d_in[3],
        (const __nv_bfloat16*)d_in[4], (const __nv_bfloat16*)d_in[6], (const __nv_bfloat16*)d_in[7], (const __nv_bfloat16*)d_in[8],
        (const __nv_bfloat16*)d_in[9], (__nv_bfloat16*)d_out, 0u);
}
```

```cpp
#include <cuda_runtime.h>
#include <cuda.h>
#include <cuda_bf16.h>
#include <stdint.h>

namespace {

constexpr int D_MODEL = 640;
constexpr int NH = 32;
constexpr int SK = 4096;
constexpr int DH = 192;
constexpr int WIN = 1024;
constexpr int DF = 1536;
constexpr int NATT = 96, NFFN = 24, NSRC = NATT + NFFN, NRED = 10, NCTA = NSRC + NRED, NGRID = 132;
constexpr int NTHR = 320;
#define PH1SLEEP 100
#define DRY 1
#define IBURST 52
#define FBURST 30
#define WATT 7
#define WFFN 5
#define L2PROMO CU_TENSOR_MAP_L2_PROMOTION_NONE
constexpr int WMAX = 8;
constexpr int TILE = 8192;
constexpr int NSLOT = 26;
constexpr int ATT_ITEMS = 52, FFN_ITEMS = 30;
constexpr uint32_t SPIN_LIMIT = 1u << 20;

constexpr int SM_X = NSLOT * TILE;
constexpr int SM_SC = SM_X + 1280;
constexpr int SM_P = SM_SC + 4096;
constexpr int SM_PART = SM_P + 2048;
constexpr int SM_RED = SM_PART + 1024;
constexpr int SM_BAR = SM_RED + 128;
constexpr int NBAR = NSLOT + 4;
constexpr int SM_TOTAL = SM_BAR + NBAR * 8 + 1024;

struct Maps { CUtensorMap m[7]; };

__device__ __align__(128) uint32_t g_s[NATT * 3 * WIN];
__device__ __align__(128) uint32_t g_f[NRED * NSRC * 64];

#define STAMP(i) do {} while (0)
#define TS(v) do {} while (0)

__device__ __forceinline__ uint32_t smem_u32(const void* p) { return (uint32_t)__cvta_generic_to_shared(p); }
__device__ __forceinline__ void mbar_init(uint32_t a, uint32_t c) { asm volatile("mbarrier.init.shared::cta.b64 [%0], %1;" ::"r"(a), "r"(c) : "memory"); }
__device__ __forceinline__ void mbar_expect(uint32_t a, uint32_t tx) { asm volatile("mbarrier.arrive.expect_tx.shared::cta.b64 _, [%0], %1;" ::"r"(a), "r"(tx) : "memory"); }
__device__ __forceinline__ void mbar_arrive(uint32_t a) { asm volatile("mbarrier.arrive.shared::cta.b64 _, [%0];" ::"r"(a) : "memory"); }
__device__ __forceinline__ void mbar_wait(uint32_t a, uint32_t parity = 0) {
    uint32_t ok, n = 0;
    do {
        asm volatile("{.reg .pred p; mbarrier.try_wait.parity.shared::cta.b64 p, [%1], %2; selp.u32 %0, 1, 0, p;}" : "=r"(ok) : "r"(a), "r"(parity) : "memory");
    } while (!ok && ++n < SPIN_LIMIT);
}
__device__ __forceinline__ void bulk_g2s(uint32_t dst, const void* src, uint32_t bytes, uint32_t mbar) {
    asm volatile("cp.async.bulk.shared::cluster.global.mbarrier::complete_tx::bytes [%0], [%1], %2, [%3];" ::"r"(dst), "l"(src), "r"(bytes), "r"(mbar) : "memory");
}
__device__ __forceinline__ void tma2d(uint32_t dst, const CUtensorMap* map, int c0, int c1, uint32_t mbar) {
    asm volatile("cp.async.bulk.tensor.2d.shared::cluster.global.mbarrier::complete_tx::bytes [%0], [%1, {%3, %4}], [%2];"
                 ::"r"(dst), "l"(map), "r"(mbar), "r"(c0), "r"(c1) : "memory");
}
__device__ __forceinline__ void ldsm4(uint32_t (&a)[4], uint32_t addr) {
    asm volatile("ldmatrix.sync.aligned.m8n8.x4.shared.b16 {%0,%1,%2,%3}, [%4];" : "=r"(a[0]), "=r"(a[1]), "=r"(a[2]), "=r"(a[3]) : "r"(addr) : "memory");
}
__device__ __forceinline__ void ldsm4t(uint32_t (&a)[4], uint32_t addr) {
    asm volatile("ldmatrix.sync.aligned.m8n8.x4.trans.shared.b16 {%0,%1,%2,%3}, [%4];" : "=r"(a[0]), "=r"(a[1]), "=r"(a[2]), "=r"(a[3]) : "r"(addr) : "memory");
}
__device__ __forceinline__ void mma16816(float (&c)[4], const uint32_t (&a)[4], uint32_t b0, uint32_t b1) {
    asm volatile("mma.sync.aligned.m16n8k16.row.col.f32.bf16.bf16.f32 {%0,%1,%2,%3}, {%4,%5,%6,%7}, {%8,%9}, {%0,%1,%2,%3};"
                 : "+f"(c[0]), "+f"(c[1]), "+f"(c[2]), "+f"(c[3]) : "r"(a[0]), "r"(a[1]), "r"(a[2]), "r"(a[3]), "r"(b0), "r"(b1));
}
__device__ __forceinline__ uint32_t lds32(uint32_t a) { uint32_t v; asm volatile("ld.shared.u32 %0, [%1];" : "=r"(v) : "r"(a) : "memory"); return v; }
__device__ __forceinline__ uint2 lds64(uint32_t a) { uint2 v; asm volatile("ld.shared.v2.u32 {%0,%1}, [%2];" : "=r"(v.x), "=r"(v.y) : "r"(a) : "memory"); return v; }
__device__ __forceinline__ void named_bar(int id, int n) { asm volatile("bar.sync %0, %1;" ::"r"(id), "r"(n) : "memory"); }
__device__ __forceinline__ void named_arrive(int id, int n) { asm volatile("bar.arrive %0, %1;" ::"r"(id), "r"(n) : "memory"); }
__device__ __forceinline__ float bf_lo(uint32_t u) { return __uint_as_float(u << 16); }
__device__ __forceinline__ float bf_hi(uint32_t u) { return __uint_as_float(u & 0xffff0000u); }
__device__ __forceinline__ float rbf(float f) { return __bfloat162float(__float2bfloat16_rn(f)); }
__device__ __forceinline__ uint32_t pack_bf(float lo, float hi) { __nv_bfloat162 v = __floats2bfloat162_rn(lo, hi); return *reinterpret_cast<uint32_t*>(&v); }
__device__ __forceinline__ uint32_t enc(float f) { uint32_t u = __float_as_uint(f); return u == 0u ? 0x80000000u : u; }
__device__ __forceinline__ void st_relaxed2(uint32_t* p, uint32_t a, uint32_t b) { asm volatile("st.relaxed.gpu.global.v2.u32 [%0], {%1,%2};" ::"l"(p), "r"(a), "r"(b) : "memory"); }
__device__ __forceinline__ void st_relaxed4(uint32_t* p, uint32_t a, uint32_t b, uint32_t c, uint32_t d) { asm volatile("st.relaxed.gpu.global.v4.u32 [%0], {%1,%2,%3,%4};" ::"l"(p), "r"(a), "r"(b), "r"(c), "r"(d) : "memory"); }
__device__ __forceinline__ uint4 ld_relaxed4(const uint32_t* p) { uint4 v; asm volatile("ld.relaxed.gpu.global.v4.u32 {%0,%1,%2,%3}, [%4];" : "=r"(v.x), "=r"(v.y), "=r"(v.z), "=r"(v.w) : "l"(p) : "memory"); return v; }
__device__ __forceinline__ bool full4(const uint4& v) { return v.x && v.y && v.z && v.w; }
__device__ __forceinline__ float gelu_tanh(float g) { return __fdividef(g, 1.f + __expf(-1.5957691216057308f * (g + 0.044715f * g * g * g))); }
__device__ __forceinline__ uint32_t opaque(uint32_t v) { uint32_t r; asm volatile("mov.u32 %0, %1;" : "=r"(r) : "r"(v)); return r; }

__device__ __forceinline__ void rows_x(int first, int par, uint32_t sb, uint32_t offT, uint32_t xfrag, uint32_t bar_full, uint32_t live, float& lo, float& hi) {
    float c0[4] = {0.f, 0.f, 0.f, 0.f}, c1[4] = {0.f, 0.f, 0.f, 0.f};
    const int n = live ? 10 : 2;
#pragma unroll 1
    for (int j = par; j < n; j += 2) {
        const int i = first + j;
        uint32_t bx[8];
#pragma unroll
        for (int kb = 0; kb < 4; kb++) { bx[2 * kb] = lds32(xfrag + j * 128 + kb * 32); bx[2 * kb + 1] = lds32(xfrag + j * 128 + kb * 32 + 16); }
        if (live) mbar_wait(bar_full + 8 * i);
        uint32_t a[4][4];
#pragma unroll
        for (int kb = 0; kb < 4; kb++) ldsm4t(a[kb], sb + i * TILE + offT + kb * 2048);
        mma16816(c0, a[0], bx[0], bx[1]); mma16816(c1, a[1], bx[2], bx[3]);
        mma16816(c0, a[2], bx[4], bx[5]); mma16816(c1, a[3], bx[6], bx[7]);
    }
    lo = c0[0] + c1[0];
    hi = c0[2] + c1[2];
}

__device__ __forceinline__ void out_tiles(int first, int par, int mb, uint32_t sb, uint32_t offT, const uint32_t (&bv)[8], uint32_t bar_full,
                                          int lane, int b, uint32_t live) {
    uint32_t* dst = g_f + (size_t)b * 64 + mb * 16 + (lane >> 2) * 2;
    const int n = live ? 10 : 2;
#pragma unroll 1
    for (int j = par; j < n; j += 2) {
        const int i = first + j;
        const int slot = i >= NSLOT ? i - NSLOT : i;
        const uint32_t ta = sb + slot * TILE + offT;
        if (live) mbar_wait(bar_full + 8 * slot, i >= NSLOT);
        uint32_t a[4][4];
#pragma unroll
        for (int kb = 0; kb < 4; kb++) ldsm4t(a[kb], ta + kb * 2048);
        float c0[4] = {0.f, 0.f, 0.f, 0.f}, c1[4] = {0.f, 0.f, 0.f, 0.f};
        mma16816(c0, a[0], bv[0], bv[1]); mma16816(c1, a[1], bv[2], bv[3]);
        mma16816(c0, a[2], bv[4], bv[5]); mma16816(c1, a[3], bv[6], bv[7]);
        if ((lane & 3) == 0 && live) st_relaxed2(dst + (size_t)j * NSRC * 64, enc(c0[0] + c1[0]), enc(c0[2] + c1[2]));
    }
}

__global__ void __launch_bounds__(NTHR, 1)
fused_decode_kernel(const __grid_constant__ Maps maps, const __nv_bfloat16* __restrict__ x, const __nv_bfloat16* __restrict__ gate_w,
                    __nv_bfloat16* __restrict__ out) {
    extern __shared__ unsigned char sm_raw[];
    const uint32_t sb = (smem_u32(sm_raw) + 1023u) & ~1023u;
    unsigned char* sm = sm_raw + (sb - smem_u32(sm_raw));
    const int tid = threadIdx.x, lane = tid & 31;
    const int warp = __shfl_sync(0xffffffffu, tid >> 5, 0);
    const int grp = blockIdx.x / 11, kk = blockIdx.x - grp * 11;
    const int b = kk == 10 ? NSRC + grp : (kk == 4 || kk == 9 ? NATT + grp * 2 + (kk == 9) : grp * 8 + kk - (kk > 4));
    if (b >= NCTA) return;
    float* s_part = reinterpret_cast<float*>(sm + SM_PART);
    float* s_red = reinterpret_cast<float*>(sm + SM_RED);
    const uint32_t bar_full = sb + SM_BAR, bar_empty = bar_full + 8 * NSLOT, bar_x = bar_empty + 8 * 3;
    if (tid == 0) STAMP(0);

    if (b >= NSRC) {
        const int ct = b - NSRC;
        float* s_rf = reinterpret_cast<float*>(sm);
        if (warp == 8) {
            float s = 0.f;
#pragma unroll
            for (int i = 0; i < 5; i++) {
                const uint2 gx = __ldg(reinterpret_cast<const uint2*>(x) + i * 32 + lane);
                const uint2 gw = __ldg(reinterpret_cast<const uint2*>(gate_w) + i * 32 + lane);
                s += rbf(bf_lo(gx.x) * bf_lo(gw.x)); s += rbf(bf_hi(gx.x) * bf_hi(gw.x));
                s += rbf(bf_lo(gx.y) * bf_lo(gw.y)); s += rbf(bf_hi(gx.y) * bf_hi(gw.y));
            }
#pragma unroll
            for (int o = 16; o; o >>= 1) s += __shfl_xor_sync(0xffffffffu, s, o);
            if (lane == 0) {
                const float g = rbf(1.f / (1.f + __expf(-rbf(s))));
                s_red[0] = g;
                s_red[1] = rbf(1.f - g);
            }
            __syncwarp();
            named_arrive(2, 288);
        } else if (warp < 8) {
            const int sg = tid >> 4;
            const long long tstart = clock64();
            uint32_t* in = g_f + (size_t)ct * NSRC * 64 + tid * 4;
#pragma unroll 1
            for (int pass = DRY ? 0 : 1; pass < 2; pass++) {
                const uint32_t live = opaque(pass);
                uint4 v[8];
#pragma unroll
                for (int k = 0; k < 8; k++) v[k] = make_uint4(0u, 0u, 0u, 0u);
                uint32_t n = 0;
                if (live) named_bar(2, 288);
                while (live) {
                    v[0] = ld_relaxed4(in);
                    if (__any_sync(0xffffffffu, full4(v[0])) || ++n >= SPIN_LIMIT) break;
                    __nanosleep(PH1SLEEP);
                }
                TS(ta);
                uint32_t pend = full4(v[0]) ? 0xfeu : 0xffu;
                if (sg >= 8) pend &= 0x7fu;
                if (!live) pend = 0;
                n = 0;
                while (pend && ++n < SPIN_LIMIT) {
#pragma unroll
                    for (int k = 0; k < 8; k++) if (pend >> k & 1) v[k] = ld_relaxed4(in + k * 1024);
#pragma unroll
                    for (int k = 0; k < 8; k++) if (full4(v[k])) pend &= ~(1u << k);
                }
                TS(tb);
                const uint32_t rounds = n;
                float a[8];
                a[0] = ((__uint_as_float(v[0].x) + __uint_as_float(v[1].x)) + (__uint_as_float(v[2].x) + __uint_as_float(v[3].x))) + (__uint_as_float(v[4].x) + __uint_as_float(v[5].x));
                a[1] = ((__uint_as_float(v[0].y) + __uint_as_float(v[1].y)) + (__uint_as_float(v[2].y) + __uint_as_float(v[3].y))) + (__uint_as_float(v[4].y) + __uint_as_float(v[5].y));
                a[2] = ((__uint_as_float(v[0].z) + __uint_as_float(v[1].z)) + (__uint_as_float(v[2].z) + __uint_as_float(v[3].z))) + (__uint_as_float(v[4].z) + __uint_as_float(v[5].z));
                a[3] = ((__uint_as_float(v[0].w) + __uint_as_float(v[1].w)) + (__uint_as_float(v[2].w) + __uint_as_float(v[3].w))) + (__uint_as_float(v[4].w) + __uint_as_float(v[5].w));
                a[4] = __uint_as_float(v[6].x) + __uint_as_float(v[7].x);
                a[5] = __uint_as_float(v[6].y) + __uint_as_float(v[7].y);
                a[6] = __uint_as_float(v[6].z) + __uint_as_float(v[7].z);
                a[7] = __uint_as_float(v[6].w) + __uint_as_float(v[7].w);
                __syncwarp();
#pragma unroll
                for (int j = 0; j < 8; j++) a[j] += __shfl_xor_sync(0xffffffffu, a[j], 16);
                *reinterpret_cast<float4*>(s_rf + pass * 1024 + (warp * 2 + (lane >> 4)) * 64 + (lane & 15) * 4) =
                    lane < 16 ? make_float4(a[0], a[1], a[2], a[3]) : make_float4(a[4], a[5], a[6], a[7]);
                named_bar(1, 256);
                TS(tc);
                if (tid < 64) {
                    float sa = 0.f, sf = 0.f;
#pragma unroll
                    for (int w = 0; w < 8; w++) { sa += s_rf[pass * 1024 + (w * 2) * 64 + tid]; sf += s_rf[pass * 1024 + (w * 2 + 1) * 64 + tid]; }
                    const float r = rbf(s_red[0] * rbf(sa)) + rbf(s_red[1] * rbf(sf));
                    if (live) out[ct * 64 + (tid & 48) + ((tid & 15) >> 1) + ((tid & 1) << 3)] = __float2bfloat16_rn(r);
                }
                TS(td);
                if (live) {
#pragma unroll
                    for (int k = 0; k < 8; k++) if (k < 7 || sg < 8) st_relaxed4(in + k * 1024, 0u, 0u, 0u, 0u);
                }
            }
        }
        return;
    }

    const bool att = b < NATT;
    if (warp >= 8) {
        const int nitems = att ? ATT_ITEMS : FFN_ITEMS;
        const int W = att ? WATT : WFFN;
        const int h = b / 3, r = b - 3 * h, f = b - NATT;
        const int kvrow = h * SK + (SK - WIN);
        if (lane == 0) {
            const CUtensorMap* m0 = &maps.m[att ? 0 : 4];
            const int c0 = (att ? b : f) * 64;
#pragma unroll
            for (int k = 0; k < WMAX / 2; k++) {
                const int i = 2 * k + (warp - 8);
                mbar_init(bar_full + 8 * i, 1);
                asm volatile("fence.mbarrier_init.release.cluster;" ::: "memory");
                if (i < W) {
                    mbar_expect(bar_full + 8 * i, TILE);
                    tma2d(sb + i * TILE, m0, c0, i * 64, bar_full + 8 * i);
                }
                if (k == 0) STAMP(8 + (warp - 8));
            }
        }
        __syncwarp();
        named_bar(0, NTHR);
        if (lane == 0) {
            const int W0 = W < WMAX ? W : WMAX;
#pragma unroll 1
            for (int i = W0 + ((W0 ^ warp) & 1); i < nitems; i += 2) {
                int map, c0, c1;
                if (att) {
                    if (i < 10) { map = 0; c0 = b * 64; c1 = i * 64; }
                    else if (i < 26) { map = 1; c0 = r * 64; c1 = kvrow + (i - 10) * 64; }
                    else if (i < 42) { map = 2; c0 = r * 64; c1 = kvrow + (i - 26) * 64; }
                    else { map = 3; c0 = (i - 42) * 64; c1 = b * 64; }
                } else {
                    if (i < 10) { map = 4; c0 = f * 64; c1 = i * 64; }
                    else if (i < 20) { map = 5; c0 = f * 64; c1 = (i - 10) * 64; }
                    else { map = 6; c0 = (i - 20) * 64; c1 = f * 64; }
                }
                const int j = i - W;
                if (j >= 0 && i < (att ? IBURST : FBURST)) mbar_wait(bar_full + 8 * (j >= NSLOT ? j - NSLOT : j), j >= NSLOT);
                int slot = i;
                if (i >= NSLOT) { slot = i - NSLOT; mbar_wait(bar_empty + (slot < 10 ? 0 : (slot < 16 ? 8 : 16))); }
                mbar_expect(bar_full + 8 * slot, TILE);
                tma2d(sb + slot * TILE, &maps.m[map], c0, c1, bar_full + 8 * slot);
            }
        }
        return;
    }

    const int par = warp >> 2, mb = warp & 3, g = lane >> 2, t = lane & 3;
    const uint32_t offT = (lane & 7) * 128 + (lane >> 4) * 1024 + (((2 * mb + ((lane >> 3) & 1)) ^ (lane & 7)) << 4);
    const uint32_t xfrag = sb + SM_X + t * 4;
    if (lane == 0) {
        if (warp == 0) {
            mbar_init(bar_x, 1);
            asm volatile("fence.mbarrier_init.release.cluster;" ::: "memory");
            mbar_expect(bar_x, 1280);
            bulk_g2s(sb + SM_X, x, 1280, bar_x);
        } else {
            const int i0 = WMAX + (warp - 1) * 3;
#pragma unroll
            for (int k = 0; k < 3; k++) mbar_init(bar_full + 8 * (i0 + k), warp == 7 ? 8 : 1);
            asm volatile("fence.mbarrier_init.release.cluster;" ::: "memory");
        }
    }
    __syncwarp();
    named_bar(0, NTHR);
    const int h = b / 3, r = b - 3 * h;
#pragma unroll 1
    for (int pass = DRY ? 0 : 1; pass < 2; pass++) {
    const uint32_t live = opaque(pass);
    if (live) mbar_wait(bar_x);
    uint32_t bv[8];

    if (!att) {
        float lo, hi;
        rows_x(0, par, sb, offT, xfrag, bar_full, live, lo, hi);
        if (lane == 0 && live) mbar_arrive(bar_empty);
        if (t == 0) { s_part[par * 64 + mb * 16 + g] = lo; s_part[par * 64 + mb * 16 + g + 8] = hi; }
        rows_x(10, par, sb, offT, xfrag, bar_full, live, lo, hi);
        if (t == 0) { s_part[128 + par * 64 + mb * 16 + g] = lo; s_part[128 + par * 64 + mb * 16 + g + 8] = hi; }
        named_bar(1, 256);
        if (tid == 0 && live) STAMP(1);
#pragma unroll
        for (int j = 0; j < 8; j++) {
            const int c = j * 8 + 2 * t;
            const float2 g0 = *reinterpret_cast<const float2*>(s_part + c), g1 = *reinterpret_cast<const float2*>(s_part + 64 + c);
            const float2 u0 = *reinterpret_cast<const float2*>(s_part + 128 + c), u1 = *reinterpret_cast<const float2*>(s_part + 192 + c);
            bv[j] = pack_bf(rbf(gelu_tanh(rbf(g0.x + g1.x))) * rbf(u0.x + u1.x), rbf(gelu_tanh(rbf(g0.y + g1.y))) * rbf(u0.y + u1.y));
        }
        out_tiles(20, par, mb, sb, offT, bv, bar_full, lane, b, live);
        if (tid == 0 && live) STAMP(6);
        named_bar(1, 256);
        continue;
    }

    {
        float lo, hi;
        rows_x(0, par, sb, offT, xfrag, bar_full, live, lo, hi);
        if (lane == 0 && live) mbar_arrive(bar_empty);
        if (t == 0) { s_part[par * 64 + mb * 16 + g] = lo; s_part[par * 64 + mb * 16 + g + 8] = hi; }
        named_bar(1, 256);
#pragma unroll
        for (int j = 0; j < 8; j++) {
            const int c = j * 8 + 2 * t;
            const float2 u0 = *reinterpret_cast<const float2*>(s_part + c), u1 = *reinterpret_cast<const float2*>(s_part + 64 + c);
            bv[j] = pack_bf(u0.x + u1.x, u0.y + u1.y);
        }
    }
    if (tid == 0 && live) STAMP(1);
    {
        const uint32_t offN = (mb * 16 + (lane & 7) + (((lane >> 3) & 1) << 3)) * 128 + (((lane >> 4) ^ (lane & 7)) << 4);
        const int peer = t == 1 ? (r == 2 ? 0 : r + 1) : (r == 0 ? 2 : r - 1);
        uint32_t* dst = g_s + ((size_t)(h * 3 + peer) * 3 + r) * WIN + mb * 16 + g * 2;
        float2* sdst = reinterpret_cast<float2*>(sm + SM_SC) + mb * 8 + g;
        const int n = live ? 16 : 2;
#pragma unroll 1
        for (int j = par; j < n; j += 2) {
            const int i = 10 + j;
            const uint32_t ta = sb + i * TILE + offN;
            if (live) mbar_wait(bar_full + 8 * i);
            uint32_t a[4][4];
#pragma unroll
            for (int kb = 0; kb < 4; kb++) ldsm4(a[kb], ta ^ (kb << 5));
            float c0[4] = {0.f, 0.f, 0.f, 0.f}, c1[4] = {0.f, 0.f, 0.f, 0.f};
            mma16816(c0, a[0], bv[0], bv[1]); mma16816(c1, a[1], bv[2], bv[3]);
            mma16816(c0, a[2], bv[4], bv[5]); mma16816(c1, a[3], bv[6], bv[7]);
            const float lo = c0[0] + c1[0], hi = c0[2] + c1[2];
            if (t == 0) sdst[j * 32] = make_float2(lo, hi);
            else if (t < 3 && live) st_relaxed2(dst + j * 64, enc(lo), enc(hi));
            if (lane == 0 && (j == 4 + par || j == 14 + par)) mbar_arrive(bar_empty + (j < 6 ? 8 : 16));
        }
    }
    named_bar(1, 256);
    if (tid == 0 && live) STAMP(2);
    {
        const float4 own = reinterpret_cast<const float4*>(sm + SM_SC)[tid];
        uint32_t* ma = g_s + ((size_t)b * 3 + (r == 0 ? 1 : 0)) * WIN + tid * 4;
        uint32_t* mc = g_s + ((size_t)b * 3 + (r == 2 ? 1 : 2)) * WIN + tid * 4;
        uint4 pa, pc;
        uint32_t n = 0;
        pa = pc = make_uint4(0u, 0u, 0u, 0u);
        while (live) {
            pa = ld_relaxed4(ma); pc = ld_relaxed4(mc);
            if ((full4(pa) && full4(pc)) || ++n >= SPIN_LIMIT) break;
        }
        float s[4];
        const float o4[4] = {own.x, own.y, own.z, own.w};
        const float a4[4] = {__uint_as_float(pa.x), __uint_as_float(pa.y), __uint_as_float(pa.z), __uint_as_float(pa.w)};
        const float c4[4] = {__uint_as_float(pc.x), __uint_as_float(pc.y), __uint_as_float(pc.z), __uint_as_float(pc.w)};
        float m = -INFINITY;
#pragma unroll
        for (int k = 0; k < 4; k++) {
            const float first = r == 2 ? a4[k] + c4[k] : a4[k] + o4[k];
            const float last = r == 2 ? o4[k] : c4[k];
            s[k] = rbf(rbf(first + last) * 0.07216878364870322f);
            m = fmaxf(m, s[k]);
        }
#pragma unroll
        for (int o = 16; o; o >>= 1) m = fmaxf(m, __shfl_xor_sync(0xffffffffu, m, o));
        if (lane == 0) s_red[warp] = m;
        named_bar(1, 256);
        if (tid == 0 && live) STAMP(3);
        {
            const float4 m0 = *reinterpret_cast<const float4*>(s_red), m1 = *reinterpret_cast<const float4*>(s_red + 4);
            m = fmaxf(fmaxf(fmaxf(m0.x, m0.y), fmaxf(m0.z, m0.w)), fmaxf(fmaxf(m1.x, m1.y), fmaxf(m1.z, m1.w)));
        }
        float l = 0.f;
#pragma unroll
        for (int k = 0; k < 4; k++) { s[k] = __expf(s[k] - m); l += s[k]; }
#pragma unroll
        for (int o = 16; o; o >>= 1) l += __shfl_xor_sync(0xffffffffu, l, o);
        if (lane == 0) s_red[8 + warp] = l;
        named_bar(1, 256);
        {
            const float4 l0 = *reinterpret_cast<const float4*>(s_red + 8), l1 = *reinterpret_cast<const float4*>(s_red + 12);
            l = ((l0.x + l0.y) + (l0.z + l0.w)) + ((l1.x + l1.y) + (l1.z + l1.w));
        }
        const float inv = 1.f / l;
        reinterpret_cast<uint2*>(sm + SM_P)[tid] = make_uint2(pack_bf(s[0] * inv, s[2] * inv), pack_bf(s[1] * inv, s[3] * inv));
        named_bar(1, 256);
    }
    if (tid == 0 && live) STAMP(4);
    {
        float c0[4] = {0.f, 0.f, 0.f, 0.f}, c1[4] = {0.f, 0.f, 0.f, 0.f};
        const uint32_t pfrag = sb + SM_P + t * 8;
        const int n = live ? 16 : 2;
#pragma unroll 1
        for (int j = par; j < n; j += 2) {
            uint2 bp[4];
#pragma unroll
            for (int kb = 0; kb < 4; kb++) bp[kb] = lds64(pfrag + j * 128 + kb * 32);
            if (live) mbar_wait(bar_full + 8 * j, 1);
            uint32_t a[4][4];
#pragma unroll
            for (int kb = 0; kb < 4; kb++) ldsm4t(a[kb], sb + j * TILE + offT + kb * 2048);
            mma16816(c0, a[0], bp[0].x, bp[0].y); mma16816(c1, a[1], bp[1].x, bp[1].y);
            mma16816(c0, a[2], bp[2].x, bp[2].y); mma16816(c1, a[3], bp[3].x, bp[3].y);
        }
        if (t == 0) { s_part[par * 64 + mb * 16 + g] = c0[0] + c1[0]; s_part[par * 64 + mb * 16 + g + 8] = c0[2] + c1[2]; }
        named_bar(1, 256);
#pragma unroll
        for (int j = 0; j < 8; j++) {
            const int c = j * 8 + 2 * t;
            const float2 u0 = *reinterpret_cast<const float2*>(s_part + c), u1 = *reinterpret_cast<const float2*>(s_part + 64 + c);
            bv[j] = pack_bf(u0.x + u1.x, u0.y + u1.y);
        }
    }
    if (tid == 0 && live) STAMP(5);
    out_tiles(42, par, mb, sb, offT, bv, bar_full, lane, b, live);
    if (tid == 128 && live) STAMP(6);
    if (live) {
        st_relaxed4(g_s + ((size_t)b * 3 + (r == 0 ? 1 : 0)) * WIN + tid * 4, 0u, 0u, 0u, 0u);
        st_relaxed4(g_s + ((size_t)b * 3 + (r == 2 ? 1 : 2)) * WIN + tid * 4, 0u, 0u, 0u, 0u);
    } else named_bar(1, 256);
    if (tid == 0 && !live) STAMP(7);
    }
}

typedef CUresult (*EncodeFn)(CUtensorMap*, CUtensorMapDataType, cuuint32_t, void*, const cuuint64_t*, const cuuint64_t*, const cuuint32_t*,
                             const cuuint32_t*, CUtensorMapInterleave, CUtensorMapSwizzle, CUtensorMapL2promotion, CUtensorMapFloatOOBfill);

}

extern "C" void kernel_launch(void* const* d_in, const int* in_sizes, int n_in, void* d_out, int out_size) {
    static EncodeFn encode = nullptr;
    if (!encode) {
        void* fn = nullptr;
        cudaDriverEntryPointQueryResult st;
        cudaGetDriverEntryPoint("cuTensorMapEncodeTiled", &fn, cudaEnableDefault, &st);
        encode = (EncodeFn)fn;
        cudaFuncSetAttribute(fused_decode_kernel, cudaFuncAttributeMaxDynamicSharedMemorySize, SM_TOTAL);
    }
    Maps maps;
    const int src[7] = {3, 1, 2, 4, 6, 7, 8};
    const cuuint64_t cols[7] = {NH * DH, DH, DH, D_MODEL, DF, DF, D_MODEL};
    const cuuint64_t rows[7] = {D_MODEL, (cuuint64_t)NH * SK, (cuuint64_t)NH * SK, NH * DH, D_MODEL, D_MODEL, DF};
    for (int i = 0; i < 7; i++) {
        const cuuint64_t dim[2] = {cols[i], rows[i]};
        const cuuint64_t stride[1] = {cols[i] * 2};
        const cuuint32_t box[2] = {64, 64}, es[2] = {1, 1};
        encode(&maps.m[i], CU_TENSOR_MAP_DATA_TYPE_BFLOAT16, 2, d_in[src[i]], dim, stride, box, es, CU_TENSOR_MAP_INTERLEAVE_NONE,
               CU_TENSOR_MAP_SWIZZLE_128B, L2PROMO, CU_TENSOR_MAP_FLOAT_OOB_FILL_NONE);
    }
    fused_decode_kernel<<<NGRID, NTHR, SM_TOTAL>>>(maps, (const __nv_bfloat16*)d_in[0], (const __nv_bfloat16*)d_in[9], (__nv_bfloat16*)d_out);
}
```

```cpp
#include <cuda_runtime.h>
#include <cuda.h>
#include <cuda_bf16.h>
#include <stdint.h>

namespace {

constexpr int D_MODEL = 640;
constexpr int NH = 32;
constexpr int SK = 4096;
constexpr int DH = 192;
constexpr int WIN = 1024;
constexpr int DF = 1536;
constexpr int NATT = 96, NFFN = 24, NSRC = NATT + NFFN, NSPARE = 12, NCTA = NSRC + NSPARE, NBLK = 40;
constexpr int NTHR = 320;
#define PAR 0
#define FULLP 8
#define PH1SLEEP 100
#define KC 2
#define WATT 8
#define WFFN 4
constexpr int WMAX = 8;
constexpr int TILE = 8192;
constexpr int NSLOT = 26;
constexpr int ATT_ITEMS = 52, FFN_ITEMS = 30;
constexpr uint32_t SPIN_LIMIT = 1u << 20;

constexpr int SM_X = NSLOT * TILE;
constexpr int SM_SC = SM_X + 1280;
constexpr int SM_P = SM_SC + 4096;
constexpr int SM_PART = SM_P + 2048;
constexpr int SM_RED = SM_PART + 1024;
constexpr int SM_BAR = SM_RED + 128;
constexpr int NBAR = NSLOT + 5;
constexpr int SM_TOTAL = SM_BAR + NBAR * 8 + 1024;

struct Maps { CUtensorMap m[7]; };

__device__ __align__(128) uint32_t g_s[NATT * 3 * WIN];
__device__ __align__(128) uint32_t g_f[NBLK * NSRC * 16];
__device__ unsigned int g_ticket;

#define STAMP(i) do {} while (0)
#define TS(v) do {} while (0)

__device__ __forceinline__ uint32_t smem_u32(const void* p) { return (uint32_t)__cvta_generic_to_shared(p); }
__device__ __forceinline__ void mbar_init(uint32_t a, uint32_t c) { asm volatile("mbarrier.init.shared::cta.b64 [%0], %1;" ::"r"(a), "r"(c) : "memory"); }
__device__ __forceinline__ void mbar_fence_init() { asm volatile("fence.mbarrier_init.release.cluster;" ::: "memory"); }
__device__ __forceinline__ void mbar_expect(uint32_t a, uint32_t tx) { asm volatile("mbarrier.arrive.expect_tx.shared::cta.b64 _, [%0], %1;" ::"r"(a), "r"(tx) : "memory"); }
__device__ __forceinline__ void mbar_arrive(uint32_t a) { asm volatile("mbarrier.arrive.shared::cta.b64 _, [%0];" ::"r"(a) : "memory"); }
__device__ __forceinline__ void mbar_wait(uint32_t a, uint32_t parity = 0) {
    uint32_t ok, n = 0;
    do {
        asm volatile("{.reg .pred p; mbarrier.try_wait.parity.shared::cta.b64 p, [%1], %2; selp.u32 %0, 1, 0, p;}" : "=r"(ok) : "r"(a), "r"(parity) : "memory");
    } while (!ok && ++n < SPIN_LIMIT);
}
__device__ __forceinline__ uint32_t mbar_test(uint32_t a, uint32_t parity) {
    uint32_t ok;
    asm volatile("{.reg .pred p; mbarrier.test_wait.parity.shared::cta.b64 p, [%1], %2; selp.u32 %0, 1, 0, p;}" : "=r"(ok) : "r"(a), "r"(parity) : "memory");
    return ok;
}
__device__ __forceinline__ void bulk_g2s(uint32_t dst, const void* src, uint32_t bytes, uint32_t mbar) {
    asm volatile("cp.async.bulk.shared::cluster.global.mbarrier::complete_tx::bytes [%0], [%1], %2, [%3];" ::"r"(dst), "l"(src), "r"(bytes), "r"(mbar) : "memory");
}
#define EF 1
__device__ __forceinline__ void tma2d(uint32_t dst, const CUtensorMap* map, int c0, int c1, uint32_t mbar) {
    asm volatile("cp.async.bulk.tensor.2d.shared::cluster.global.mbarrier::complete_tx::bytes.L2::cache_hint [%0], [%1, {%3, %4}], [%2], %5;"
                 ::"r"(dst), "l"(map), "r"(mbar), "r"(c0), "r"(c1), "l"(0x12F0000000000000ull) : "memory");
}
__device__ __forceinline__ void ldsm4(uint32_t (&a)[4], uint32_t addr) {
    asm volatile("ldmatrix.sync.aligned.m8n8.x4.shared.b16 {%0,%1,%2,%3}, [%4];" : "=r"(a[0]), "=r"(a[1]), "=r"(a[2]), "=r"(a[3]) : "r"(addr) : "memory");
}
__device__ __forceinline__ void ldsm4t(uint32_t (&a)[4], uint32_t addr) {
    asm volatile("ldmatrix.sync.aligned.m8n8.x4.trans.shared.b16 {%0,%1,%2,%3}, [%4];" : "=r"(a[0]), "=r"(a[1]), "=r"(a[2]), "=r"(a[3]) : "r"(addr) : "memory");
}
__device__ __forceinline__ void mma16816(float (&c)[4], const uint32_t (&a)[4], uint32_t b0, uint32_t b1) {
    asm volatile("mma.sync.aligned.m16n8k16.row.col.f32.bf16.bf16.f32 {%0,%1,%2,%3}, {%4,%5,%6,%7}, {%8,%9}, {%0,%1,%2,%3};"
                 : "+f"(c[0]), "+f"(c[1]), "+f"(c[2]), "+f"(c[3]) : "r"(a[0]), "r"(a[1]), "r"(a[2]), "r"(a[3]), "r"(b0), "r"(b1));
}
__device__ __forceinline__ uint32_t lds32(uint32_t a) { uint32_t v; asm volatile("ld.shared.u32 %0, [%1];" : "=r"(v) : "r"(a) : "memory"); return v; }
__device__ __forceinline__ uint2 lds64(uint32_t a) { uint2 v; asm volatile("ld.shared.v2.u32 {%0,%1}, [%2];" : "=r"(v.x), "=r"(v.y) : "r"(a) : "memory"); return v; }
__device__ __forceinline__ void named_bar(int id, int n) { asm volatile("bar.sync %0, %1;" ::"r"(id), "r"(n) : "memory"); }
__device__ __forceinline__ float bf_lo(uint32_t u) { return __uint_as_float(u << 16); }
__device__ __forceinline__ float bf_hi(uint32_t u) { return __uint_as_float(u & 0xffff0000u); }
__device__ __forceinline__ float rbf(float f) { return __bfloat162float(__float2bfloat16_rn(f)); }
__device__ __forceinline__ uint32_t pack_bf(float lo, float hi) { __nv_bfloat162 v = __floats2bfloat162_rn(lo, hi); return *reinterpret_cast<uint32_t*>(&v); }
__device__ __forceinline__ uint32_t enc(float f, uint32_t) { uint32_t u = __float_as_uint(f); return u == 0u ? 0x80000000u : u; }
__device__ __forceinline__ bool full4(const uint4& v, uint32_t) { return v.x && v.y && v.z && v.w; }
__device__ __forceinline__ void st_relaxed2(uint32_t* p, uint32_t a, uint32_t b) { asm volatile("st.relaxed.gpu.global.v2.u32 [%0], {%1,%2};" ::"l"(p), "r"(a), "r"(b) : "memory"); }
__device__ __forceinline__ void st_relaxed4(uint32_t* p, uint32_t a, uint32_t b, uint32_t c, uint32_t d) { asm volatile("st.relaxed.gpu.global.v4.u32 [%0], {%1,%2,%3,%4};" ::"l"(p), "r"(a), "r"(b), "r"(c), "r"(d) : "memory"); }
__device__ __forceinline__ void ld_relaxed4_if(uint4& v, const uint32_t* p, uint32_t c) {
    asm volatile("{.reg .pred p; setp.ne.u32 p, %5, 0; @p ld.relaxed.gpu.global.v4.u32 {%0,%1,%2,%3}, [%4];}"
                 : "+r"(v.x), "+r"(v.y), "+r"(v.z), "+r"(v.w) : "l"(p), "r"(c) : "memory");
}
__device__ __forceinline__ float gelu_tanh(float g) { return __fdividef(g, 1.f + __expf(-1.5957691216057308f * (g + 0.044715f * g * g * g))); }
__device__ __forceinline__ uint32_t opaque(uint32_t v) { uint32_t r; asm volatile("mov.u32 %0, %1;" : "=r"(r) : "r"(v)); return r; }

__device__ __forceinline__ void rows_x(int first, int par, uint32_t sb, uint32_t offT, uint32_t xfrag, uint32_t bar_full, float& lo, float& hi) {
    float c0[4] = {0.f, 0.f, 0.f, 0.f}, c1[4] = {0.f, 0.f, 0.f, 0.f};
#pragma unroll 1
    for (int j = par; j < 10; j += 2) {
        const int i = first + j;
        uint32_t bx[8];
#pragma unroll
        for (int kb = 0; kb < 4; kb++) { bx[2 * kb] = lds32(xfrag + j * 128 + kb * 32); bx[2 * kb + 1] = lds32(xfrag + j * 128 + kb * 32 + 16); }
        mbar_wait(bar_full + 8 * (i < KC ? NSLOT + 4 : i));
        uint32_t a[4][4];
#pragma unroll
        for (int kb = 0; kb < 4; kb++) ldsm4t(a[kb], sb + i * TILE + offT + kb * 2048);
        mma16816(c0, a[0], bx[0], bx[1]); mma16816(c1, a[1], bx[2], bx[3]);
        mma16816(c0, a[2], bx[4], bx[5]); mma16816(c1, a[3], bx[6], bx[7]);
    }
    lo = c0[0] + c1[0];
    hi = c0[2] + c1[2];
}

__device__ __forceinline__ void out_tiles(int first, int par, int mb, uint32_t sb, uint32_t offT, const uint32_t (&bv)[8], uint32_t bar_full,
                                          int lane, int b, uint32_t tag) {
    uint32_t* dst = g_f + ((size_t)mb * NSRC + b) * 16 + (lane >> 2) * 2;
#pragma unroll 1
    for (int j = par; j < 10; j += 2) {
        const int i = first + j;
        const int slot = i >= NSLOT ? i - NSLOT : i;
        const uint32_t ta = sb + slot * TILE + offT;
        mbar_wait(bar_full + 8 * slot, i >= NSLOT + KC);
        uint32_t a[4][4];
#pragma unroll
        for (int kb = 0; kb < 4; kb++) ldsm4t(a[kb], ta + kb * 2048);
        float c0[4] = {0.f, 0.f, 0.f, 0.f}, c1[4] = {0.f, 0.f, 0.f, 0.f};
        mma16816(c0, a[0], bv[0], bv[1]); mma16816(c1, a[1], bv[2], bv[3]);
        mma16816(c0, a[2], bv[4], bv[5]); mma16816(c1, a[3], bv[6], bv[7]);
        if ((lane & 3) == 0) st_relaxed2(dst + (size_t)j * NSRC * 64, enc(c0[0] + c1[0], tag), enc(c0[2] + c1[2], tag));
    }
}

__device__ __forceinline__ void reduce_block(int blk, uint32_t tag, int lane, const __nv_bfloat16* __restrict__ x,
                                             const __nv_bfloat16* __restrict__ gate_w, __nv_bfloat16* __restrict__ out) {
    float s = 0.f;
#pragma unroll
    for (int i = 0; i < 5; i++) {
        const uint2 gx = __ldg(reinterpret_cast<const uint2*>(x) + i * 32 + lane);
        const uint2 gw = __ldg(reinterpret_cast<const uint2*>(gate_w) + i * 32 + lane);
        s += rbf(bf_lo(gx.x) * bf_lo(gw.x)); s += rbf(bf_hi(gx.x) * bf_hi(gw.x));
        s += rbf(bf_lo(gx.y) * bf_lo(gw.y)); s += rbf(bf_hi(gx.y) * bf_hi(gw.y));
    }
#pragma unroll
    for (int o = 16; o; o >>= 1) s += __shfl_xor_sync(0xffffffffu, s, o);
    const float ga = rbf(1.f / (1.f + __expf(-rbf(s)))), gf = rbf(1.f - ga);
    uint32_t* in = g_f + (size_t)blk * NSRC * 16 + lane * 4;
    const bool b4 = lane & 16, b3 = lane & 8, b2 = lane & 4;
    const int pos = (lane & 3) * 4 + ((lane >> 2) & 3);
    __nv_bfloat16* op = out + blk * 16 + (pos >> 1) + ((pos & 1) << 3);
#pragma unroll 1
    for (int pass = 0; pass < 2; pass++) {
        const uint32_t live = opaque(pass);
        uint4 v[15];
#pragma unroll
        for (int k = 0; k < 15; k++) v[k] = make_uint4(PAR ? tag ^ 1u : 0u, 0u, 0u, 0u);
        uint32_t n = 0, pend = live ? 0x7fffu : 0u;
        bool tight = false;
        while (__any_sync(0xffffffffu, pend != 0u) && ++n < SPIN_LIMIT) {
            const uint32_t m = (tight || (n & (FULLP - 1)) == 1) ? pend : (pend & 1u);
#pragma unroll
            for (int k = 0; k < 15; k++) ld_relaxed4_if(v[k], in + k * 128, m & (1u << k));
#pragma unroll
            for (int k = 0; k < 15; k++) pend &= full4(v[k], tag) ? ~(1u << k) : ~0u;
            if (!tight) {
                tight = __any_sync(0xffffffffu, !(pend & 1u));
                if (!tight) __nanosleep(PH1SLEEP);
            }
        }
        TS(tb);
#define RSUM(c) ((((__uint_as_float(v[0].c) + __uint_as_float(v[1].c)) + (__uint_as_float(v[2].c) + __uint_as_float(v[3].c))) + \
                 ((__uint_as_float(v[4].c) + __uint_as_float(v[5].c)) + (__uint_as_float(v[6].c) + __uint_as_float(v[7].c)))) + \
                 ((__uint_as_float(v[8].c) + __uint_as_float(v[9].c)) + (__uint_as_float(v[10].c) + __uint_as_float(v[11].c))))
#define FSUM(c) ((__uint_as_float(v[12].c) + __uint_as_float(v[13].c)) + __uint_as_float(v[14].c))
        const float a[4] = {RSUM(x), RSUM(y), RSUM(z), RSUM(w)}, f[4] = {FSUM(x), FSUM(y), FSUM(z), FSUM(w)};
        float t[4];
#pragma unroll
        for (int j = 0; j < 4; j++) t[j] = (b4 ? f[j] : a[j]) + __shfl_xor_sync(0xffffffffu, b4 ? a[j] : f[j], 16);
        const float u0 = (b3 ? t[2] : t[0]) + __shfl_xor_sync(0xffffffffu, b3 ? t[0] : t[2], 8);
        const float u1 = (b3 ? t[3] : t[1]) + __shfl_xor_sync(0xffffffffu, b3 ? t[1] : t[3], 8);
        const float z = rbf((b4 ? gf : ga) * rbf((b2 ? u1 : u0) + __shfl_xor_sync(0xffffffffu, b2 ? u0 : u1, 4)));
        const float zo = __shfl_xor_sync(0xffffffffu, z, 16);
        if (live && !b4) *op = __float2bfloat16_rn(z + zo);
        TS(td);
        if (live) {
#pragma unroll
            for (int k = 0; k < 15; k++) st_relaxed4(in + k * 128, 0u, 0u, 0u, 0u);
        }
    }
}

__global__ void __launch_bounds__(NTHR, 1)
fused_decode_kernel(const __nv_bfloat16* __restrict__ wq, const __nv_bfloat16* __restrict__ wg, const __nv_bfloat16* __restrict__ x,
                    const __nv_bfloat16* __restrict__ gate_w, __nv_bfloat16* __restrict__ out, const __grid_constant__ Maps maps) {
    extern __shared__ unsigned char sm_raw[];
    const uint32_t sb = (smem_u32(sm_raw) + 1023u) & ~1023u;
    unsigned char* sm = sm_raw + (sb - smem_u32(sm_raw));
    const int tid = threadIdx.x, lane = tid & 31;
    const int warp = __shfl_sync(0xffffffffu, tid >> 5, 0);
    const int grp = blockIdx.x / 11, kk = blockIdx.x - grp * 11;
    const int b = kk == 10 ? NSRC + grp : (kk == 4 || kk == 9 ? NATT + grp * 2 + (kk == 9) : grp * 8 + kk - (kk > 4));
    if (tid < 256 && b < NSRC) {
        const int row = tid >> 3, ch = tid & 7;
        const int pitch = b < NATT ? NH * DH : DF;
        const __nv_bfloat16* src = (b < NATT ? wq + b * 64 : wg + (b - NATT) * 64) + (size_t)row * pitch + ch * 8;
        const uint32_t dst = sb + row * 128 + ((ch ^ (row & 7)) << 4);
#pragma unroll
        for (int k = 0; k < 2 * KC; k++)
            asm volatile("cp.async.cg.shared.global [%0], [%1], 16;" ::"r"(dst + k * 4096), "l"(src + (size_t)k * 32 * pitch) : "memory");
    }
    float* s_part = reinterpret_cast<float*>(sm + SM_PART);
    float* s_red = reinterpret_cast<float*>(sm + SM_RED);
    volatile uint32_t* s_tag = reinterpret_cast<volatile uint32_t*>(sm + SM_RED) + 16;
    const uint32_t bar_full = sb + SM_BAR, bar_empty = bar_full + 8 * NSLOT, bar_x = bar_empty + 8 * 3;
    if (tid == 0) STAMP(0);

    if (b >= NSRC) {
        uint32_t tag = 0;
        const int s = b - NSRC, j = 9 - (s >> 2) - 3 * warp;
        if (j >= 0) reduce_block(j * 4 + (s & 3), tag, lane, x, gate_w, out);
        return;
    }

    const bool att = b < NATT;
    if (warp >= 8) {
        const int nitems = att ? ATT_ITEMS : FFN_ITEMS;
        const int W = att ? WATT : WFFN;
        const int h = b / 3, r = b - 3 * h, f = b - NATT;
        const int kvrow = h * SK + (SK - WIN);
        if (lane == 0) {
            const CUtensorMap* m0 = &maps.m[att ? 0 : 4];
            const int c0 = (att ? b : f) * 64;
#pragma unroll
            for (int k = 0; k < WMAX / 2; k++) {
                const int i = (2 * k + (warp - 8) + KC) % WMAX;
                mbar_init(bar_full + 8 * i, 1);
                mbar_fence_init();
                if (i >= KC && i < W) {
                    mbar_expect(bar_full + 8 * i, TILE);
                    tma2d(sb + i * TILE, m0, c0, i * 64, bar_full + 8 * i);
                }
                if (k == 0) STAMP(8 + (warp - 8));
            }
        }
        __syncwarp();
        named_bar(0, NTHR);
        if (warp == 8) {
            int my = lane, next = W;
            uint32_t n = 0;
            while (next < nitems && ++n < SPIN_LIMIT * 8) {
                uint32_t landed = 0;
                if (lane < W) landed = mbar_test(bar_full + 8 * (my >= NSLOT ? my - NSLOT : (my < KC ? NSLOT + 4 : my)), my >= NSLOT + KC);
                uint32_t m = __ballot_sync(0xffffffffu, landed);
#pragma unroll 1
                while (m && next < nitems) {
                    const int i = next++;
                    if (lane == __ffs(m) - 1) my = i;
                    m &= m - 1;
                    if (lane == 0) {
                        int map, c0, c1;
                        if (att) {
                            if (i < 10) { map = 0; c0 = b * 64; c1 = i * 64; }
                            else if (i < 26) { map = 1; c0 = r * 64; c1 = kvrow + (i - 10) * 64; }
                            else if (i < 42) { map = 2; c0 = r * 64; c1 = kvrow + (i - 26) * 64; }
                            else { map = 3; c0 = (i - 42) * 64; c1 = b * 64; }
                        } else {
                            if (i < 10) { map = 4; c0 = f * 64; c1 = i * 64; }
                            else if (i < 20) { map = 5; c0 = f * 64; c1 = (i - 10) * 64; }
                            else { map = 6; c0 = (i - 20) * 64; c1 = f * 64; }
                        }
                        int slot = i;
                        if (i >= NSLOT) { slot = i - NSLOT; mbar_wait(bar_empty + (slot < 10 ? 0 : (slot < 16 ? 8 : 16))); }
                        mbar_expect(bar_full + 8 * slot, TILE);
                        tma2d(sb + slot * TILE, &maps.m[map], c0, c1, bar_full + 8 * slot);
                    }
                    __syncwarp();
                }
            }
        }
        return;
    }

    const int par = warp >> 2, mb = warp & 3, g = lane >> 2, t = lane & 3;
    const uint32_t offT = (lane & 7) * 128 + (lane >> 4) * 1024 + (((2 * mb + ((lane >> 3) & 1)) ^ (lane & 7)) << 4);
    const uint32_t xfrag = sb + SM_X + t * 4;
    if (lane == 0) {
        if (warp == 0) {
            mbar_init(bar_x, 1);
            mbar_init(bar_x + 8, 256);
            mbar_fence_init();
            mbar_expect(bar_x, 1280);
            bulk_g2s(sb + SM_X, x, 1280, bar_x);
        } else {
            const int i0 = WMAX + (warp - 1) * 3;
#pragma unroll
            for (int k = 0; k < 3; k++) mbar_init(bar_full + 8 * (i0 + k), warp == 7 ? 8 : 1);
            mbar_fence_init();
        }
    }
    __syncwarp();
    named_bar(0, NTHR);
    asm volatile("cp.async.mbarrier.arrive.noinc.shared::cta.b64 [%0];" ::"r"(bar_x + 8) : "memory");
    const int h = b / 3, r = b - 3 * h;
    mbar_wait(bar_x);
    uint32_t bv[8];

    if (!att) {
        float lo, hi;
        rows_x(0, par, sb, offT, xfrag, bar_full, lo, hi);
        if (lane == 0) mbar_arrive(bar_empty);
        if (t == 0) { s_part[par * 64 + mb * 16 + g] = lo; s_part[par * 64 + mb * 16 + g + 8] = hi; }
        rows_x(10, par, sb, offT, xfrag, bar_full, lo, hi);
        if (t == 0) { s_part[128 + par * 64 + mb * 16 + g] = lo; s_part[128 + par * 64 + mb * 16 + g + 8] = hi; }
        named_bar(1, 256);
        if (tid == 0) STAMP(1);
#pragma unroll
        for (int j = 0; j < 8; j++) {
            const int c = j * 8 + 2 * t;
            const float2 g0 = *reinterpret_cast<const float2*>(s_part + c), g1 = *reinterpret_cast<const float2*>(s_part + 64 + c);
            const float2 u0 = *reinterpret_cast<const float2*>(s_part + 128 + c), u1 = *reinterpret_cast<const float2*>(s_part + 192 + c);
            bv[j] = pack_bf(rbf(gelu_tanh(rbf(g0.x + g1.x))) * rbf(u0.x + u1.x), rbf(gelu_tanh(rbf(g0.y + g1.y))) * rbf(u0.y + u1.y));
        }
        out_tiles(20, par, mb, sb, offT, bv, bar_full, lane, b, PAR ? *s_tag : 0u);
        if (tid == 0) STAMP(6);
        return;
    }

    {
        float lo, hi;
        rows_x(0, par, sb, offT, xfrag, bar_full, lo, hi);
        if (lane == 0) mbar_arrive(bar_empty);
        if (t == 0) { s_part[par * 64 + mb * 16 + g] = lo; s_part[par * 64 + mb * 16 + g + 8] = hi; }
        named_bar(1, 256);
#pragma unroll
        for (int j = 0; j < 8; j++) {
            const int c = j * 8 + 2 * t;
            const float2 u0 = *reinterpret_cast<const float2*>(s_part + c), u1 = *reinterpret_cast<const float2*>(s_part + 64 + c);
            bv[j] = pack_bf(u0.x + u1.x, u0.y + u1.y);
        }
    }
    const uint32_t tag = PAR ? *s_tag : 0u;
    if (tid == 0) STAMP(1);
    {
        const uint32_t offN = (mb * 16 + (lane & 7) + (((lane >> 3) & 1) << 3)) * 128 + (((lane >> 4) ^ (lane & 7)) << 4);
        const int peer = t == 1 ? (r == 2 ? 0 : r + 1) : (r == 0 ? 2 : r - 1);
        uint32_t* dst = g_s + ((size_t)(h * 3 + peer) * 3 + r) * WIN + mb * 16 + g * 2;
        uint2* sdst = reinterpret_cast<uint2*>(sm + SM_SC) + mb * 8 + g;
#pragma unroll 1
        for (int j = par; j < 16; j += 2) {
            const int i = 10 + j;
            const uint32_t ta = sb + i * TILE + offN;
            mbar_wait(bar_full + 8 * i);
            uint32_t a[4][4];
#pragma unroll
            for (int kb = 0; kb < 4; kb++) ldsm4(a[kb], ta ^ (kb << 5));
            float c0[4] = {0.f, 0.f, 0.f, 0.f}, c1[4] = {0.f, 0.f, 0.f, 0.f};
            mma16816(c0, a[0], bv[0], bv[1]); mma16816(c1, a[1], bv[2], bv[3]);
            mma16816(c0, a[2], bv[4], bv[5]); mma16816(c1, a[3], bv[6], bv[7]);
            const uint32_t lo = enc(c0[0] + c1[0], tag), hi = enc(c0[2] + c1[2], tag);
            if (t == 0) sdst[j * 32] = make_uint2(lo, hi);
            else if (t < 3) st_relaxed2(dst + j * 64, lo, hi);
            if (lane == 0 && (j == 4 + par || j == 14 + par)) mbar_arrive(bar_empty + (j < 6 ? 8 : 16));
        }
    }
    named_bar(1, 256);
    if (tid == 0) STAMP(2);
    {
        const float4 own = reinterpret_cast<const float4*>(sm + SM_SC)[tid];
        uint32_t* ma = g_s + ((size_t)b * 3 + (r == 0 ? 1 : 0)) * WIN + tid * 4;
        uint32_t* mc = g_s + ((size_t)b * 3 + (r == 2 ? 1 : 2)) * WIN + tid * 4;
        uint4 pa = make_uint4(0u, 0u, 0u, 0u), pc = pa;
        uint32_t n = 0, pend = 3u;
        while (pend && ++n < SPIN_LIMIT) {
            ld_relaxed4_if(pa, ma, pend & 1u); ld_relaxed4_if(pc, mc, pend & 2u);
            pend = (full4(pa, tag) ? 0u : 1u) | (full4(pc, tag) ? 0u : 2u);
        }
        float s[4];
        const float o4[4] = {own.x, own.y, own.z, own.w};
        const float a4[4] = {__uint_as_float(pa.x), __uint_as_float(pa.y), __uint_as_float(pa.z), __uint_as_float(pa.w)};
        const float c4[4] = {__uint_as_float(pc.x), __uint_as_float(pc.y), __uint_as_float(pc.z), __uint_as_float(pc.w)};
        float m = -INFINITY;
#pragma unroll
        for (int k = 0; k < 4; k++) {
            const float first = r == 2 ? a4[k] + c4[k] : a4[k] + o4[k];
            const float last = r == 2 ? o4[k] : c4[k];
            s[k] = rbf(rbf(first + last) * 0.07216878364870322f);
            m = fmaxf(m, s[k]);
        }
#pragma unroll
        for (int o = 16; o; o >>= 1) m = fmaxf(m, __shfl_xor_sync(0xffffffffu, m, o));
        if (lane == 0) s_red[warp] = m;
        named_bar(1, 256);
        if (tid == 0) STAMP(3);
        {
            const float4 m0 = *reinterpret_cast<const float4*>(s_red), m1 = *reinterpret_cast<const float4*>(s_red + 4);
            m = fmaxf(fmaxf(fmaxf(m0.x, m0.y), fmaxf(m0.z, m0.w)), fmaxf(fmaxf(m1.x, m1.y), fmaxf(m1.z, m1.w)));
        }
        float l = 0.f;
#pragma unroll
        for (int k = 0; k < 4; k++) { s[k] = __expf(s[k] - m); l += s[k]; }
#pragma unroll
        for (int o = 16; o; o >>= 1) l += __shfl_xor_sync(0xffffffffu, l, o);
        if (lane == 0) s_red[8 + warp] = l;
        named_bar(1, 256);
        {
            const float4 l0 = *reinterpret_cast<const float4*>(s_red + 8), l1 = *reinterpret_cast<const float4*>(s_red + 12);
            l = ((l0.x + l0.y) + (l0.z + l0.w)) + ((l1.x + l1.y) + (l1.z + l1.w));
        }
        const float inv = 1.f / l;
        reinterpret_cast<uint2*>(sm + SM_P)[tid] = make_uint2(pack_bf(s[0] * inv, s[2] * inv), pack_bf(s[1] * inv, s[3] * inv));
        named_bar(1, 256);
        st_relaxed4(ma, 0u, 0u, 0u, 0u);
        st_relaxed4(mc, 0u, 0u, 0u, 0u);
    }
    if (tid == 0) STAMP(4);
    {
        float c0[4] = {0.f, 0.f, 0.f, 0.f}, c1[4] = {0.f, 0.f, 0.f, 0.f};
        const uint32_t pfrag = sb + SM_P + t * 8;
#pragma unroll 1
        for (int j = par; j < 16; j += 2) {
            uint2 bp[4];
#pragma unroll
            for (int kb = 0; kb < 4; kb++) bp[kb] = lds64(pfrag + j * 128 + kb * 32);
            mbar_wait(bar_full + 8 * j, j >= KC);
            uint32_t a[4][4];
#pragma unroll
            for (int kb = 0; kb < 4; kb++) ldsm4t(a[kb], sb + j * TILE + offT + kb * 2048);
            mma16816(c0, a[0], bp[0].x, bp[0].y); mma16816(c1, a[1], bp[1].x, bp[1].y);
            mma16816(c0, a[2], bp[2].x, bp[2].y); mma16816(c1, a[3], bp[3].x, bp[3].y);
        }
        if (t == 0) { s_part[par * 64 + mb * 16 + g] = c0[0] + c1[0]; s_part[par * 64 + mb * 16 + g + 8] = c0[2] + c1[2]; }
        named_bar(1, 256);
#pragma unroll
        for (int j = 0; j < 8; j++) {
            const int c = j * 8 + 2 * t;
            const float2 u0 = *reinterpret_cast<const float2*>(s_part + c), u1 = *reinterpret_cast<const float2*>(s_part + 64 + c);
            bv[j] = pack_bf(u0.x + u1.x, u0.y + u1.y);
        }
    }
    if (tid == 0) STAMP(5);
    out_tiles(42, par, mb, sb, offT, bv, bar_full, lane, b, tag);
    if (tid == 128) STAMP(6);
}

typedef CUresult (*EncodeFn)(CUtensorMap*, CUtensorMapDataType, cuuint32_t, void*, const cuuint64_t*, const cuuint64_t*, const cuuint32_t*,
                             const cuuint32_t*, CUtensorMapInterleave, CUtensorMapSwizzle, CUtensorMapL2promotion, CUtensorMapFloatOOBfill);

}

extern "C" void kernel_launch(void* const* d_in, const int* in_sizes, int n_in, void* d_out, int out_size) {
    static EncodeFn encode = nullptr;
    if (!encode) {
        void* fn = nullptr;
        cudaDriverEntryPointQueryResult st;
        cudaGetDriverEntryPoint("cuTensorMapEncodeTiled", &fn, cudaEnableDefault, &st);
        encode = (EncodeFn)fn;
        cudaFuncSetAttribute(fused_decode_kernel, cudaFuncAttributeMaxDynamicSharedMemorySize, SM_TOTAL);
    }
    Maps maps;
    const int src[7] = {3, 1, 2, 4, 6, 7, 8};
    const cuuint64_t cols[7] = {NH * DH, DH, DH, D_MODEL, DF, DF, D_MODEL};
    const cuuint64_t rows[7] = {D_MODEL, (cuuint64_t)NH * SK, (cuuint64_t)NH * SK, NH * DH, D_MODEL, D_MODEL, DF};
    for (int i = 0; i < 7; i++) {
        const cuuint64_t dim[2] = {cols[i], rows[i]};
        const cuuint64_t stride[1] = {cols[i] * 2};
        const cuuint32_t box[2] = {64, 64}, es[2] = {1, 1};
        encode(&maps.m[i], CU_TENSOR_MAP_DATA_TYPE_BFLOAT16, 2, d_in[src[i]], dim, stride, box, es, CU_TENSOR_MAP_INTERLEAVE_NONE,
               CU_TENSOR_MAP_SWIZZLE_128B, CU_TENSOR_MAP_L2_PROMOTION_NONE, CU_TENSOR_MAP_FLOAT_OOB_FILL_NONE);
    }
    fused_decode_kernel<<<NCTA, NTHR, SM_TOTAL>>>((const __nv_bfloat16*)d_in[3], (const __nv_bfloat16*)d_in[6], (const __nv_bfloat16*)d_in[0],
                                                  (const __nv_bfloat16*)d_in[9], (__nv_bfloat16*)d_out, maps);
}
```

```cpp
#include <cuda_runtime.h>
#include <cuda.h>
#include <cuda_bf16.h>
#include <stdint.h>

namespace {

constexpr int D_MODEL = 640;
constexpr int NH = 32;
constexpr int SK = 4096;
constexpr int DH = 192;
constexpr int WIN = 1024;
constexpr int DF = 1536;
constexpr int NATT = 96, NFFN = 24, NSRC = NATT + NFFN;
constexpr int CS = 8, NCL = 15, NOWN = 10, NCTA = CS * NCL;
constexpr int NTHR = 320;
#define KC 2
#define WATT 10
#define WFFN 12
#define WFN 8
#define WA2 12
#define EARLY 0
#define EF 1
#define LEAD 7
#define DA 299
#define DL 251
#define DF_ 443
#define DFL 188
#define NFE 28
#define DN 443
#define BA 5
#define BF 3
#define SLOWP 2500
#define DUEO 900
#define DUEH 900
constexpr int WMAX = 8;
constexpr int TILE = 8192;
constexpr int NSLOT = 26;
constexpr int NB = 12;
constexpr uint32_t SPIN_LIMIT = 1u << 20;

constexpr int SM_X = NSLOT * TILE;
constexpr int SM_SC = SM_X + 1280;
constexpr int SM_P = SM_SC + 4096;
constexpr int SM_PART = SM_P + 2048;
constexpr int SM_RED = SM_PART + 1024;
constexpr int SM_VEC = SM_RED + 128;
constexpr int SM_FIN = SM_VEC + NB * 128;
constexpr int SM_BAR = SM_FIN + 20 * 72 * 4;
constexpr int B_EMPTY = NSLOT, B_X = NSLOT + 4, B_CP = NSLOT + 5, B_GO = NSLOT + 6, B_GOH = NSLOT + 7, B_FINA = NSLOT + 8, B_FINB = NSLOT + 9, B_VEC = NSLOT + 10;
constexpr int NBAR = B_VEC + 2 * NB;
constexpr int SM_TOTAL = SM_BAR + NBAR * 8 + 1024;

struct Maps { CUtensorMap m[7]; };

__device__ __align__(128) uint32_t g_s[NATT * 3 * WIN];
__device__ __align__(128) uint32_t g_v[NOWN * NSRC * 32];

#define STAMP(i) do {} while (0)

__device__ __forceinline__ uint32_t smem_u32(const void* p) { return (uint32_t)__cvta_generic_to_shared(p); }
__device__ __forceinline__ void mbar_init(uint32_t a, uint32_t c) { asm volatile("mbarrier.init.shared::cta.b64 [%0], %1;" ::"r"(a), "r"(c) : "memory"); }
__device__ __forceinline__ void mbar_fence_init() { asm volatile("fence.mbarrier_init.release.cluster;" ::: "memory"); }
__device__ __forceinline__ void mbar_expect(uint32_t a, uint32_t tx) { asm volatile("mbarrier.arrive.expect_tx.shared::cta.b64 _, [%0], %1;" ::"r"(a), "r"(tx) : "memory"); }
__device__ __forceinline__ void mbar_arrive(uint32_t a) { asm volatile("mbarrier.arrive.shared::cta.b64 _, [%0];" ::"r"(a) : "memory"); }
__device__ __forceinline__ void mbar_arrive_remote(uint32_t a) { asm volatile("mbarrier.arrive.release.cluster.shared::cluster.b64 _, [%0];" ::"r"(a) : "memory"); }
__device__ __forceinline__ void mbar_wait(uint32_t a, uint32_t parity = 0) {
    uint32_t ok, n = 0;
    do {
        asm volatile("{.reg .pred p; mbarrier.try_wait.parity.shared::cta.b64 p, [%1], %2; selp.u32 %0, 1, 0, p;}" : "=r"(ok) : "r"(a), "r"(parity) : "memory");
    } while (!ok && ++n < SPIN_LIMIT);
}
__device__ __forceinline__ void mbar_wait_cluster(uint32_t a, uint32_t parity = 0) {
    uint32_t ok, n = 0;
    do {
        asm volatile("{.reg .pred p; mbarrier.try_wait.parity.acquire.cluster.shared::cta.b64 p, [%1], %2; selp.u32 %0, 1, 0, p;}" : "=r"(ok) : "r"(a), "r"(parity) : "memory");
    } while (!ok && ++n < SPIN_LIMIT);
}
__device__ __forceinline__ uint32_t mbar_test(uint32_t a, uint32_t parity) {
    uint32_t ok;
    asm volatile("{.reg .pred p; mbarrier.test_wait.parity.shared::cta.b64 p, [%1], %2; selp.u32 %0, 1, 0, p;}" : "=r"(ok) : "r"(a), "r"(parity) : "memory");
    return ok;
}
__device__ __forceinline__ uint32_t mapa(uint32_t a, uint32_t rank) { uint32_t r; asm("mapa.shared::cluster.u32 %0, %1, %2;" : "=r"(r) : "r"(a), "r"(rank)); return r; }
__device__ __forceinline__ void st_async2(uint32_t a, float x, float y, uint32_t mbar) {
    asm volatile("st.async.weak.shared::cluster.mbarrier::complete_tx::bytes.v2.f32 [%0], {%1,%2}, [%3];" ::"r"(a), "f"(x), "f"(y), "r"(mbar) : "memory");
}
__device__ __forceinline__ void cluster_arrive() { asm volatile("barrier.cluster.arrive.relaxed.aligned;" ::: "memory"); }
__device__ __forceinline__ void cluster_wait() { asm volatile("barrier.cluster.wait.acquire.aligned;" ::: "memory"); }
__device__ __forceinline__ void bulk_g2s(uint32_t dst, const void* src, uint32_t bytes, uint32_t mbar) {
    asm volatile("cp.async.bulk.shared::cluster.global.mbarrier::complete_tx::bytes [%0], [%1], %2, [%3];" ::"r"(dst), "l"(src), "r"(bytes), "r"(mbar) : "memory");
}
__device__ __forceinline__ void tma2d(uint32_t dst, const CUtensorMap* map, int c0, int c1, uint32_t mbar) {
    asm volatile("cp.async.bulk.tensor.2d.shared::cluster.global.mbarrier::complete_tx::bytes.L2::cache_hint [%0], [%1, {%3, %4}], [%2], %5;"
                 ::"r"(dst), "l"(map), "r"(mbar), "r"(c0), "r"(c1), "l"(0x12F0000000000000ull) : "memory");
}
__device__ __forceinline__ void ldsm4(uint32_t (&a)[4], uint32_t addr) {
    asm volatile("ldmatrix.sync.aligned.m8n8.x4.shared.b16 {%0,%1,%2,%3}, [%4];" : "=r"(a[0]), "=r"(a[1]), "=r"(a[2]), "=r"(a[3]) : "r"(addr) : "memory");
}
__device__ __forceinline__ void ldsm4t(uint32_t (&a)[4], uint32_t addr) {
    asm volatile("ldmatrix.sync.aligned.m8n8.x4.trans.shared.b16 {%0,%1,%2,%3}, [%4];" : "=r"(a[0]), "=r"(a[1]), "=r"(a[2]), "=r"(a[3]) : "r"(addr) : "memory");
}
__device__ __forceinline__ void mma16816(float (&c)[4], const uint32_t (&a)[4], uint32_t b0, uint32_t b1) {
    asm volatile("mma.sync.aligned.m16n8k16.row.col.f32.bf16.bf16.f32 {%0,%1,%2,%3}, {%4,%5,%6,%7}, {%8,%9}, {%0,%1,%2,%3};"
                 : "+f"(c[0]), "+f"(c[1]), "+f"(c[2]), "+f"(c[3]) : "r"(a[0]), "r"(a[1]), "r"(a[2]), "r"(a[3]), "r"(b0), "r"(b1));
}
__device__ __forceinline__ uint32_t lds32(uint32_t a) { uint32_t v; asm volatile("ld.shared.u32 %0, [%1];" : "=r"(v) : "r"(a) : "memory"); return v; }
__device__ __forceinline__ float ldsf(uint32_t a) { float v; asm volatile("ld.shared.f32 %0, [%1];" : "=f"(v) : "r"(a) : "memory"); return v; }
__device__ __forceinline__ uint2 lds64(uint32_t a) { uint2 v; asm volatile("ld.shared.v2.u32 {%0,%1}, [%2];" : "=r"(v.x), "=r"(v.y) : "r"(a) : "memory"); return v; }
__device__ __forceinline__ uint4 lds128(uint32_t a) { uint4 v; asm volatile("ld.shared.v4.u32 {%0,%1,%2,%3}, [%4];" : "=r"(v.x), "=r"(v.y), "=r"(v.z), "=r"(v.w) : "r"(a) : "memory"); return v; }
__device__ __forceinline__ void sts128(uint32_t a, const uint4& v) { asm volatile("st.shared.v4.u32 [%0], {%1,%2,%3,%4};" ::"r"(a), "r"(v.x), "r"(v.y), "r"(v.z), "r"(v.w) : "memory"); }
__device__ __forceinline__ void named_bar(int id, int n) { asm volatile("bar.sync %0, %1;" ::"r"(id), "r"(n) : "memory"); }
__device__ __forceinline__ float bf_lo(uint32_t u) { return __uint_as_float(u << 16); }
__device__ __forceinline__ float bf_hi(uint32_t u) { return __uint_as_float(u & 0xffff0000u); }
__device__ __forceinline__ float rbf(float f) { return __bfloat162float(__float2bfloat16_rn(f)); }
__device__ __forceinline__ uint32_t pack_bf(float lo, float hi) { __nv_bfloat162 v = __floats2bfloat162_rn(lo, hi); return *reinterpret_cast<uint32_t*>(&v); }
__device__ __forceinline__ uint32_t encu(uint32_t u) { return u == 0u ? 0x80000000u : u; }
__device__ __forceinline__ uint32_t enc(float f) { return encu(__float_as_uint(f)); }
__device__ __forceinline__ bool full4(const uint4& v) { return v.x && v.y && v.z && v.w; }
__device__ __forceinline__ void st_relaxed1(uint32_t* p, uint32_t a) { asm volatile("st.relaxed.gpu.global.u32 [%0], %1;" ::"l"(p), "r"(a) : "memory"); }
__device__ __forceinline__ void st_relaxed2(uint32_t* p, uint32_t a, uint32_t b) { asm volatile("st.relaxed.gpu.global.v2.u32 [%0], {%1,%2};" ::"l"(p), "r"(a), "r"(b) : "memory"); }
__device__ __forceinline__ void st_relaxed4(uint32_t* p, uint32_t a, uint32_t b, uint32_t c, uint32_t d) { asm volatile("st.relaxed.gpu.global.v4.u32 [%0], {%1,%2,%3,%4};" ::"l"(p), "r"(a), "r"(b), "r"(c), "r"(d) : "memory"); }
__device__ __forceinline__ void ld_relaxed4_if(uint4& v, const uint32_t* p, uint32_t c) {
    asm volatile("{.reg .pred p; setp.ne.u32 p, %5, 0; @p ld.relaxed.gpu.global.v4.u32 {%0,%1,%2,%3}, [%4];}"
                 : "+r"(v.x), "+r"(v.y), "+r"(v.z), "+r"(v.w) : "l"(p), "r"(c) : "memory");
}
__device__ __forceinline__ float gelu_tanh(float g) { return __fdividef(g, 1.f + __expf(-1.5957691216057308f * (g + 0.044715f * g * g * g))); }

__device__ __forceinline__ int slot_of(int i) { return i >= 2 * NSLOT ? i - 2 * NSLOT : (i >= NSLOT ? i - NSLOT : i); }
__device__ __forceinline__ uint32_t bidx(int i) { return i < KC ? B_CP : slot_of(i); }
__device__ __forceinline__ uint32_t bpar(int i) { return i >= NSLOT + KC && !(i >= 2 * NSLOT + KC); }

__device__ __noinline__ float2 rows(int first, int n, int par, uint32_t sb, uint32_t offT, uint32_t frag, uint32_t barv, uint32_t vstep) {
    float c0[4] = {0.f, 0.f, 0.f, 0.f}, c1[4] = {0.f, 0.f, 0.f, 0.f};
    const uint32_t bar = sb + SM_BAR;
#pragma unroll 1
    for (int j = par; j < n; j += 2) {
        const int i = first + j;
        const uint32_t ta = sb + slot_of(i) * TILE + offT, bt = bar + 8 * bidx(i), pt = bpar(i), bv = barv + j * vstep;
        uint32_t ok, cnt = 0;
        do {
            asm volatile("{.reg .pred p, q; mbarrier.try_wait.parity.shared::cta.b64 p, [%1], 0; mbarrier.try_wait.parity.shared::cta.b64 q, [%2], %3;"
                         " and.pred p, p, q; selp.u32 %0, 1, 0, p;}" : "=r"(ok) : "r"(bv), "r"(bt), "r"(pt) : "memory");
        } while (!ok && ++cnt < SPIN_LIMIT);
        uint32_t a[4][4], bx[8];
#pragma unroll
        for (int kb = 0; kb < 4; kb++) {
            ldsm4t(a[kb], ta + kb * 2048);
            bx[2 * kb] = lds32(frag + j * 128 + kb * 32); bx[2 * kb + 1] = lds32(frag + j * 128 + kb * 32 + 16);
        }
        mma16816(c0, a[0], bx[0], bx[1]); mma16816(c1, a[1], bx[2], bx[3]);
        mma16816(c0, a[2], bx[4], bx[5]); mma16816(c1, a[3], bx[6], bx[7]);
    }
    return make_float2(c0[0] + c1[0], c0[2] + c1[2]);
}

__device__ __forceinline__ uint32_t gtime() { uint32_t t; asm volatile("mov.u32 %0, %%globaltimer_lo;" : "=r"(t)); return t; }
__device__ __noinline__ void poll_slices(uint32_t* in, uint32_t dst, uint32_t barv, int lane, uint32_t t0, uint32_t due) {
    in += lane * 4;
    dst += lane * 16;
    barv += (lane >> 3) * 8;
    uint4 v[3];
#pragma unroll
    for (int k = 0; k < 3; k++) v[k] = make_uint4(0u, 0u, 0u, 0u);
    uint32_t pend = 7u, n = 0;
    while (pend && ++n < SPIN_LIMIT) {
#pragma unroll
        for (int k = 0; k < 3; k++) ld_relaxed4_if(v[k], in + k * 128, pend & (1u << k));
#pragma unroll
        for (int k = 0; k < 3; k++)
            if ((pend & (1u << k)) && full4(v[k])) {
                sts128(dst + k * 512, v[k]);
                mbar_arrive(barv + k * 32);
                st_relaxed4(in + k * 128, 0u, 0u, 0u, 0u);
                pend &= ~(1u << k);
            }
        const uint32_t t1 = gtime() - t0;
        if (t1 < due) {
            const uint32_t until = min(due, t1 + SLOWP);
            for (int k = 0; k < 64 && gtime() - t0 < until; k++) __nanosleep(100);
        }
    }
}

__global__ void __launch_bounds__(NTHR, 1)
fused_decode_kernel(const __nv_bfloat16* __restrict__ wq, const __nv_bfloat16* __restrict__ wg, const __nv_bfloat16* __restrict__ x,
                    const __nv_bfloat16* __restrict__ gate_w, __nv_bfloat16* __restrict__ out, const __grid_constant__ Maps maps,
                    const void* kc, const void* vc, const void* wo, const void* wu, const void* wd) {
    extern __shared__ unsigned char sm_raw[];
    const uint32_t sb = (smem_u32(sm_raw) + 1023u) & ~1023u;
    unsigned char* sm = sm_raw + (sb - smem_u32(sm_raw));
    const int tid = threadIdx.x, lane = tid & 31;
    const int warp = __shfl_sync(0xffffffffu, tid >> 5, 0);
    const int cl = blockIdx.x >> 3, rk = blockIdx.x & 7;
    const bool own = cl < NOWN;
    const bool att = own ? (rk & 3) != 3 : (rk != 7 || cl == NCL - 1);
    const int b = own ? (att ? cl * 6 + rk - (rk >> 2) : NATT + cl * 2 + (rk >> 2))
                      : (att ? 6 * NOWN + (cl - NOWN) * 7 + rk : NATT + 2 * NOWN + cl - NOWN);
    if (tid < 256) {
        const int row = tid >> 3, ch = tid & 7;
        const int pitch = att ? NH * DH : DF;
        const __nv_bfloat16* src = (att ? wq + b * 64 : wg + (b - NATT) * 64) + (size_t)row * pitch + ch * 8;
        const uint32_t dst = sb + row * 128 + ((ch ^ (row & 7)) << 4);
#pragma unroll
        for (int k = 0; k < 2 * KC; k++)
            asm volatile("cp.async.cg.shared.global [%0], [%1], 16;" ::"r"(dst + k * 4096), "l"(src + (size_t)k * 32 * pitch) : "memory");
    }
    float* s_part = reinterpret_cast<float*>(sm + SM_PART);
    float* s_red = reinterpret_cast<float*>(sm + SM_RED);
    const uint32_t bar = sb + SM_BAR, bar_empty = bar + 8 * B_EMPTY;
    if (tid == 0) STAMP(0);
    const int n1 = att ? 42 : (own ? 32 : 20);
    const int nitems = own ? n1 + NB : n1;

    if (warp >= 8) {
        const int W = att ? WATT : (own ? WFFN : WFN), W2 = att ? WA2 : W;
        const int B = att ? BA : BF;
        uint32_t t0;
        asm volatile("mov.u32 %0, %%globaltimer_lo;" : "=r"(t0));
        const int h = b / 3, r = b - 3 * h, f = b - NATT;
        const int kvrow = h * SK + (SK - WIN);
        if (lane == 0) {
            const CUtensorMap* m0 = &maps.m[att ? 0 : 4];
            const int c0 = (att ? b : f) * 64;
#pragma unroll
            for (int k = 0; k < WMAX / 2; k++) {
                const int i = (2 * k + (warp - 8) + KC) % WMAX;
                mbar_init(bar + 8 * i, 1);
                mbar_fence_init();
                if (i >= KC && i < B) {
                    mbar_expect(bar + 8 * i, TILE);
                    tma2d(sb + i * TILE, m0, c0, i * 64, bar + 8 * i);
                }
                if (k == 0) STAMP(8 + (warp - 8));
            }
        }
        __syncwarp();
        named_bar(0, NTHR);
        if (own) cluster_arrive();
        if (warp == 8) {
            const int t2 = att ? 26 : 20;
            const CUtensorMap* mpa = &maps.m[att ? 0 : 4];
            const CUtensorMap* mpd = &maps.m[3];
            const int ca = (att ? b : f) * 64, cb = att ? r * 64 : ca, cc = att ? r * 64 : cl * 64, cd = cl * 64;
            const int rb = att ? kvrow - 640 : -640, rc = att ? kvrow - 26 * 64 : ((rk >> 2) * NB - 20) * 64, rd = (rk * NB - n1) * 64;
            const int lim1 = att ? 42 : 64;
            uint32_t wb = lane >= 28 ? bar_empty + (lane - 28) * 8 : bar + 8 * (lane < KC ? B_CP : lane), wp = 0;
            bool busy = lane < B || lane >= 28;
            int next = B;
            const int nl = att ? 42 : (own ? NFE : 64);
            const float inva = 1.f / (att ? DA : (own ? DF_ : DN)), invl = 1.f / (att ? DL : DFL);
            const float fa = (float)(nl - B) * (att ? DA : (own ? DF_ : DN));
            uint32_t n = 0;
            const uint32_t lt = (1u << lane) - 1u;
            while (next < nitems && ++n < SPIN_LIMIT * 8) {
                uint32_t ok = lane < (next >= n1 - EARLY ? W2 : W);
                if (busy) ok = mbar_test(wb, wp);
                const uint32_t v = __ballot_sync(0xffffffffu, ok);
                const uint32_t m = v & 0x0fffffffu;
                if (m) {
                    int lim = NSLOT;
                    if (v >> 28 & 1) lim = v >> 29 & 1 ? (lim1 != 42 ? 64 : (v >> 30 & 1 ? (v >> 31 ? 64 : 52) : 42)) : 36;
                    lim = min(lim, nitems);
                    {
                        uint32_t t1;
                        asm volatile("mov.u32 %0, %%globaltimer_lo;" : "=r"(t1));
                        const float ft = (float)(t1 - t0);
                        lim = min(lim, ft < fa ? B + (int)(ft * inva) : nl + (int)((ft - fa) * invl));
                    }
                    const int i = next + __popc(m & lt);
                    if (lane < 28) busy = busy && !ok;
                    if (ok && lane < 28 && i < lim) {
                        const bool p1 = i >= 10, p2 = i >= t2, p3 = i >= n1;
                        const CUtensorMap* mp = p3 ? mpd : mpa + (p1 ? 1 : 0) + (p2 ? 1 : 0);
                        const int c0 = p3 ? cd : (p2 ? cc : (p1 ? cb : ca));
                        const int c1 = (p3 ? rd : (p2 ? rc : (p1 ? rb : 0))) + i * 64;
                        const int slot = slot_of(i);
                        wb = bar + 8 * slot; wp = bpar(i); busy = true;
                        mbar_expect(wb, TILE);
                        tma2d(sb + slot * TILE, mp, c0, c1, wb);
                    }
                    next = min(next + __popc(m), max(lim, next));
                }
            }
        }
        else if (own) {
            if (!att) {
                poll_slices(g_v + ((size_t)cl * NSRC + NATT + (rk >> 2) * NB) * 32, sb + SM_SC, bar + 8 * (B_VEC + NB), lane, t0, (20 - BF) * DF_ + DUEH);
                if (lane == 0) STAMP(10);
            }
            poll_slices(g_v + ((size_t)cl * NSRC + rk * NB) * 32, sb + SM_VEC, bar + 8 * B_VEC, lane, t0, (42 - BA) * DA + DUEO);
            __syncwarp();
            if (lane == 0) STAMP(12);
        }
        return;
    }

    const int par = warp >> 2, mb = warp & 3, g = lane >> 2, t = lane & 3;
    const uint32_t offT = (lane & 7) * 128 + (lane >> 4) * 1024 + (((2 * mb + ((lane >> 3) & 1)) ^ (lane & 7)) << 4);
    const uint32_t xfrag = sb + SM_X + t * 4;
    if (warp == 0) {
        if (lane == 0) {
            mbar_init(bar + 8 * B_X, 1);
            mbar_init(bar + 8 * B_CP, 256);
            mbar_fence_init();
            mbar_expect(bar + 8 * B_X, 1280);
            bulk_g2s(sb + SM_X, x, 1280, bar + 8 * B_X);
        }
    } else if (lane == 0) {
#pragma unroll
        for (int k = 0; k < 8; k++) {
            const int j = warp - 1 + 7 * k, i = j < 22 ? WMAX + j : WMAX + 2 + j;
            if (j < 50) mbar_init(bar + 8 * i, i < NSLOT || (i >= B_GO && i < B_VEC) ? 1 : 8);
            if (i == B_FINA) mbar_expect(bar + 8 * B_FINA, 16 * 256);
            if (i == B_FINB) mbar_expect(bar + 8 * B_FINB, 4 * 256);
        }
        mbar_fence_init();
    }
    __syncwarp();
    named_bar(0, NTHR);
    if (own) cluster_arrive();
    asm volatile("cp.async.mbarrier.arrive.noinc.shared::cta.b64 [%0];" ::"r"(bar + 8 * B_CP) : "memory");
    const int h = b / 3, r = b - 3 * h;
    const uint32_t fin_row = mapa(sb + SM_FIN + (mb * 16 + g * 2) * 4, LEAD), fin_bar = mapa(bar + 8 * B_FINA, LEAD);
    const int pw = lane * 2;
    uint32_t* pub = g_v + ((size_t)warp * NSRC + b) * 32 + lane;

    if (!att) {
        float ga = 0.f, gf = 0.f;
        if (rk == LEAD && own) {
            float s = 0.f;
            mbar_wait(bar + 8 * B_X);
#pragma unroll
            for (int i = 0; i < 5; i++) {
                const uint2 gx = lds64(sb + SM_X + (i * 32 + lane) * 8);
                const uint2 gw = __ldg(reinterpret_cast<const uint2*>(gate_w) + i * 32 + lane);
                s += rbf(bf_lo(gx.x) * bf_lo(gw.x)); s += rbf(bf_hi(gx.x) * bf_hi(gw.x));
                s += rbf(bf_lo(gx.y) * bf_lo(gw.y)); s += rbf(bf_hi(gx.y) * bf_hi(gw.y));
            }
#pragma unroll
            for (int o = 16; o; o >>= 1) s += __shfl_xor_sync(0xffffffffu, s, o);
            ga = rbf(1.f / (1.f + __expf(-rbf(s))));
            gf = rbf(1.f - ga);
        }
        float2 y = rows(0, 10, par, sb, offT, xfrag, bar + 8 * B_X, 0);
        if (lane == 0) mbar_arrive(bar_empty);
        if (t == 0) { s_part[par * 64 + mb * 16 + g] = y.x; s_part[par * 64 + mb * 16 + g + 8] = y.y; }
        y = rows(10, 10, par, sb, offT, xfrag, bar + 8 * B_X, 0);
        if (lane == 0) mbar_arrive(bar_empty + 8);
        if (t == 0) { s_part[128 + par * 64 + mb * 16 + g] = y.x; s_part[128 + par * 64 + mb * 16 + g + 8] = y.y; }
        named_bar(1, 256);
        if (tid == 0) STAMP(1);
        {
            const float2 g0 = *reinterpret_cast<const float2*>(s_part + pw), g1 = *reinterpret_cast<const float2*>(s_part + 64 + pw);
            const float2 u0 = *reinterpret_cast<const float2*>(s_part + 128 + pw), u1 = *reinterpret_cast<const float2*>(s_part + 192 + pw);
            const uint32_t w = encu(pack_bf(rbf(gelu_tanh(rbf(g0.x + g1.x))) * rbf(u0.x + u1.x), rbf(gelu_tanh(rbf(g0.y + g1.y))) * rbf(u0.y + u1.y)));
            st_relaxed1(pub, w);
            if (warp < NOWN - 8) st_relaxed1(pub + 8 * NSRC * 32, w);
        }
        if (!own) return;
        cluster_wait();
        y = rows(20, NB, par, sb, offT, sb + SM_SC + t * 4, bar + 8 * (B_VEC + NB), 8);
        if (t == 0) st_async2(fin_row + (16 + (rk >> 2) * 2 + par) * 288, y.x, y.y, fin_bar + 8);
        if (tid == 0) STAMP(2);
        float zb = 0.f;
        const uint32_t fin = sb + SM_FIN + (lane >> 3) * 288 + (warp * 8 + (lane & 7)) * 4;
        if (rk == LEAD) {
            mbar_wait_cluster(bar + 8 * B_FINB);
            float s = ldsf(fin + 16 * 288);
            s += __shfl_xor_sync(0xffffffffu, s, 8);
            s += __shfl_xor_sync(0xffffffffu, s, 16);
            zb = rbf(gf * rbf(s));
        }
        y = rows(32, NB, par, sb, offT, sb + SM_VEC + t * 4, bar + 8 * B_VEC, 8);
        if (t == 0) st_async2(fin_row + (rk * 2 + par) * 288, y.x, y.y, fin_bar);
        if (tid == 0) STAMP(6);
        if (rk == LEAD) {
            const int p = warp * 8 + (lane & 7);
            __nv_bfloat16* op = out + cl * 64 + (p & 48) + ((p & 15) >> 1) + ((p & 1) << 3);
            mbar_wait_cluster(bar + 8 * B_FINA);
            if (tid == 0) STAMP(13);
            float s = (ldsf(fin) + ldsf(fin + 4 * 288)) + (ldsf(fin + 8 * 288) + ldsf(fin + 12 * 288));
            s += __shfl_xor_sync(0xffffffffu, s, 8);
            s += __shfl_xor_sync(0xffffffffu, s, 16);
            if (lane < 8) *op = __float2bfloat16_rn(rbf(ga * rbf(s)) + zb);
            if (tid == 0) STAMP(7);
        }
        return;
    }

    uint32_t bv[8];
    {
        const float2 y = rows(0, 10, par, sb, offT, xfrag, bar + 8 * B_X, 0);
        if (lane == 0) mbar_arrive(bar_empty);
        if (t == 0) { s_part[par * 64 + mb * 16 + g] = y.x; s_part[par * 64 + mb * 16 + g + 8] = y.y; }
        named_bar(1, 256);
#pragma unroll
        for (int j = 0; j < 8; j++) {
            const int c = j * 8 + 2 * t;
            const float2 u0 = *reinterpret_cast<const float2*>(s_part + c), u1 = *reinterpret_cast<const float2*>(s_part + 64 + c);
            bv[j] = pack_bf(u0.x + u1.x, u0.y + u1.y);
        }
    }
    if (tid == 0) STAMP(1);
    if (own) cluster_wait();
    {
        const uint32_t offN = (mb * 16 + (lane & 7) + (((lane >> 3) & 1) << 3)) * 128 + (((lane >> 4) ^ (lane & 7)) << 4);
        const int peer = t == 1 ? (r == 2 ? 0 : r + 1) : (r == 0 ? 2 : r - 1);
        uint32_t* dst = g_s + ((size_t)(h * 3 + peer) * 3 + r) * WIN + mb * 16 + g * 2;
        uint2* sdst = reinterpret_cast<uint2*>(sm + SM_SC) + mb * 8 + g;
#pragma unroll 1
        for (int j = par; j < 16; j += 2) {
            const int i = 10 + j;
            const uint32_t ta = sb + i * TILE + offN;
            mbar_wait(bar + 8 * i);
            uint32_t a[4][4];
#pragma unroll
            for (int kb = 0; kb < 4; kb++) ldsm4(a[kb], ta ^ (kb << 5));
            float c0[4] = {0.f, 0.f, 0.f, 0.f}, c1[4] = {0.f, 0.f, 0.f, 0.f};
            mma16816(c0, a[0], bv[0], bv[1]); mma16816(c1, a[1], bv[2], bv[3]);
            mma16816(c0, a[2], bv[4], bv[5]); mma16816(c1, a[3], bv[6], bv[7]);
            const uint32_t lo = enc(c0[0] + c1[0]), hi = enc(c0[2] + c1[2]);
            if (t == 0) sdst[j * 32] = make_uint2(lo, hi);
            else if (t < 3) st_relaxed2(dst + j * 64, lo, hi);
            if (lane == 0 && (j == 4 + par || j == 14 + par)) mbar_arrive(bar_empty + (j < 6 ? 8 : 16));
        }
    }
    named_bar(1, 256);
    if (tid == 0) STAMP(2);
    {
        const float4 own4 = reinterpret_cast<const float4*>(sm + SM_SC)[tid];
        uint32_t* ma = g_s + ((size_t)b * 3 + (r == 0 ? 1 : 0)) * WIN + tid * 4;
        uint32_t* mc = g_s + ((size_t)b * 3 + (r == 2 ? 1 : 2)) * WIN + tid * 4;
        uint4 pa = make_uint4(0u, 0u, 0u, 0u), pc = pa;
        uint32_t n = 0, pend = 3u;
        while (pend && ++n < SPIN_LIMIT) {
            ld_relaxed4_if(pa, ma, pend & 1u); ld_relaxed4_if(pc, mc, pend & 2u);
            pend = (full4(pa) ? 0u : 1u) | (full4(pc) ? 0u : 2u);
        }
        float s[4];
        const float o4[4] = {own4.x, own4.y, own4.z, own4.w};
        const float a4[4] = {__uint_as_float(pa.x), __uint_as_float(pa.y), __uint_as_float(pa.z), __uint_as_float(pa.w)};
        const float c4[4] = {__uint_as_float(pc.x), __uint_as_float(pc.y), __uint_as_float(pc.z), __uint_as_float(pc.w)};
        float m = -INFINITY;
#pragma unroll
        for (int k = 0; k < 4; k++) {
            const float first = r == 2 ? a4[k] + c4[k] : a4[k] + o4[k];
            const float last = r == 2 ? o4[k] : c4[k];
            s[k] = rbf(rbf(first + last) * 0.07216878364870322f);
            m = fmaxf(m, s[k]);
        }
#pragma unroll
        for (int o = 16; o; o >>= 1) m = fmaxf(m, __shfl_xor_sync(0xffffffffu, m, o));
        if (lane == 0) s_red[warp] = m;
        named_bar(1, 256);
        if (tid == 0) STAMP(3);
        {
            const float4 m0 = *reinterpret_cast<const float4*>(s_red), m1 = *reinterpret_cast<const float4*>(s_red + 4);
            m = fmaxf(fmaxf(fmaxf(m0.x, m0.y), fmaxf(m0.z, m0.w)), fmaxf(fmaxf(m1.x, m1.y), fmaxf(m1.z, m1.w)));
        }
        float l = 0.f;
#pragma unroll
        for (int k = 0; k < 4; k++) { s[k] = __expf(s[k] - m); l += s[k]; }
#pragma unroll
        for (int o = 16; o; o >>= 1) l += __shfl_xor_sync(0xffffffffu, l, o);
        if (lane == 0) s_red[8 + warp] = l;
        named_bar(1, 256);
        {
            const float4 l0 = *reinterpret_cast<const float4*>(s_red + 8), l1 = *reinterpret_cast<const float4*>(s_red + 12);
            l = ((l0.x + l0.y) + (l0.z + l0.w)) + ((l1.x + l1.y) + (l1.z + l1.w));
        }
        const float inv = 1.f / l;
        uint32_t* pp = reinterpret_cast<uint32_t*>(sm + SM_P) + (tid >> 2) * 8 + t;
        pp[0] = pack_bf(s[0] * inv, s[2] * inv);
        pp[4] = pack_bf(s[1] * inv, s[3] * inv);
        named_bar(1, 256);
        st_relaxed4(ma, 0u, 0u, 0u, 0u);
        st_relaxed4(mc, 0u, 0u, 0u, 0u);
    }
    if (tid == 0) STAMP(4);
    {
        const float2 y = rows(26, 16, par, sb, offT, sb + SM_P + t * 4, bar + 8 * B_X, 0);
        if (lane == 0) mbar_arrive(bar_empty + 24);
        if (t == 0) { s_part[par * 64 + mb * 16 + g] = y.x; s_part[par * 64 + mb * 16 + g + 8] = y.y; }
        named_bar(1, 256);
        const float2 u0 = *reinterpret_cast<const float2*>(s_part + pw), u1 = *reinterpret_cast<const float2*>(s_part + 64 + pw);
        const uint32_t w = encu(pack_bf(u0.x + u1.x, u0.y + u1.y));
        st_relaxed1(pub, w);
        if (warp < NOWN - 8) st_relaxed1(pub + 8 * NSRC * 32, w);
    }
    if (tid == 0) STAMP(5);
    if (!own) return;
    {
        const float2 y = rows(42, NB, par, sb, offT, sb + SM_VEC + t * 4, bar + 8 * B_VEC, 8);
        if (t == 0) st_async2(fin_row + (rk * 2 + par) * 288, y.x, y.y, fin_bar);
    }
    if (tid == 128) STAMP(6);
}

typedef CUresult (*EncodeFn)(CUtensorMap*, CUtensorMapDataType, cuuint32_t, void*, const cuuint64_t*, const cuuint64_t*, const cuuint32_t*,
                             const cuuint32_t*, CUtensorMapInterleave, CUtensorMapSwizzle, CUtensorMapL2promotion, CUtensorMapFloatOOBfill);

}

extern "C" void kernel_launch(void* const* d_in, const int* in_sizes, int n_in, void* d_out, int out_size) {
    static EncodeFn encode = nullptr;
    if (!encode) {
        void* fn = nullptr;
        cudaDriverEntryPointQueryResult st;
        cudaGetDriverEntryPoint("cuTensorMapEncodeTiled", &fn, cudaEnableDefault, &st);
        encode = (EncodeFn)fn;
        cudaFuncSetAttribute(fused_decode_kernel, cudaFuncAttributeMaxDynamicSharedMemorySize, SM_TOTAL);
    }
    Maps maps;
    const int src[7] = {3, 1, 2, 4, 6, 7, 8};
    const cuuint64_t cols[7] = {NH * DH, DH, DH, D_MODEL, DF, DF, D_MODEL};
    const cuuint64_t rows[7] = {D_MODEL, (cuuint64_t)NH * SK, (cuuint64_t)NH * SK, NH * DH, D_MODEL, D_MODEL, DF};
    for (int i = 0; i < 7; i++) {
        const cuuint64_t dim[2] = {cols[i], rows[i]};
        const cuuint64_t stride[1] = {cols[i] * 2};
        const cuuint32_t box[2] = {64, 64}, es[2] = {1, 1};
        encode(&maps.m[i], CU_TENSOR_MAP_DATA_TYPE_BFLOAT16, 2, d_in[src[i]], dim, stride, box, es, CU_TENSOR_MAP_INTERLEAVE_NONE,
               CU_TENSOR_MAP_SWIZZLE_128B, CU_TENSOR_MAP_L2_PROMOTION_NONE, CU_TENSOR_MAP_FLOAT_OOB_FILL_NONE);
    }
    cudaLaunchConfig_t cfg = {};
    cfg.gridDim = dim3(NCTA); cfg.blockDim = dim3(NTHR); cfg.dynamicSmemBytes = SM_TOTAL; cfg.stream = cudaStreamPerThread;
    cudaLaunchAttribute at[1];
    at[0].id = cudaLaunchAttributeClusterDimension; at[0].val.clusterDim.x = CS; at[0].val.clusterDim.y = 1; at[0].val.clusterDim.z = 1;
    cfg.attrs = at; cfg.numAttrs = 1;
    cudaLaunchKernelEx(&cfg, fused_decode_kernel, (const __nv_bfloat16*)d_in[3], (const __nv_bfloat16*)d_in[6], (const __nv_bfloat16*)d_in[0],
                       (const __nv_bfloat16*)d_in[9], (__nv_bfloat16*)d_out, maps, (const void*)d_in[1], (const void*)d_in[2], (const void*)d_in[4],
                       (const void*)d_in[7], (const void*)d_in[8]);
}
```

```cpp
#include <cuda_runtime.h>
#include <cuda.h>
#include <cuda_bf16.h>
#include <stdint.h>

namespace {

constexpr int D_MODEL = 640;
constexpr int NH = 32;
constexpr int SK = 4096;
constexpr int DH = 192;
constexpr int WIN = 1024;
constexpr int DF = 1536;
constexpr int NATT = 96, NFFN = 24, NSRC = NATT + NFFN;
constexpr int CS = 8, NCL = 15, NOWN = 10, NCTA = CS * NCL;
constexpr int NTHR = 320;
constexpr int KC = 2;
constexpr int WATT = 10;
constexpr int WFFN = 12;
constexpr int WFN = 8;
constexpr int WA2 = 12;
constexpr int LEAD = 7;
constexpr int DA = 295;
constexpr int DL = 232;
constexpr int DF_ = 520;
constexpr int DFL = 232;
constexpr int NFE = 24;
constexpr int DN = 520;
constexpr int BA = 5;
constexpr int BF = 3;
constexpr int GAP = 200;
constexpr int TOFF = 0;
constexpr int SLOWP = 2500;
constexpr int DUEO = 2000;
constexpr int DUEH = 1500;
constexpr int WMAX = 8;
constexpr int TILE = 8192;
constexpr int NSLOT = 26;
constexpr int NB = 12;
constexpr int NBA = 14;
constexpr int NBF = (96 - 6 * NBA) / 2;
constexpr int ND = NBA - NBF;
constexpr int NL = ((NBA > NB + NBF ? NBA : NB + NBF) + 3) / 4, RS = NL * 4;
constexpr uint32_t SPIN_LIMIT = 1u << 20;

constexpr int SM_X = NSLOT * TILE;
constexpr int SM_SC = SM_X + 1280;
constexpr int SM_P = SM_SC;
constexpr int SM_FIN = SM_SC + 2048;
constexpr int SM_PART = SM_SC + 3 * 4096;
constexpr int SM_RED = SM_PART + 1024;
constexpr int SM_VEC = SM_RED + 128;
constexpr int SM_BAR = SM_VEC + RS * 128;
constexpr int B_X = NSLOT, B_SC = NSLOT + 1, B_FINA = NSLOT + 2, B_FINB = NSLOT + 3, B_EMPTY = 32, B_VEC = 36, B_CP = 64;
constexpr int NBAR = 65;
constexpr int SM_TOTAL = SM_BAR + NBAR * 8 + 1024;

struct Maps { CUtensorMap m[7]; };

__device__ __align__(128) uint32_t g_s[6 * 3 * WIN];
__device__ __align__(128) uint32_t g_v[NOWN * CS * RS * 32];

__device__ __forceinline__ uint32_t smem_u32(const void* p) { return (uint32_t)__cvta_generic_to_shared(p); }
__device__ __forceinline__ void mbar_init(uint32_t a, uint32_t c) { asm volatile("mbarrier.init.shared::cta.b64 [%0], %1;" ::"r"(a), "r"(c) : "memory"); }
__device__ __forceinline__ void mbar_fence_init() { asm volatile("fence.mbarrier_init.release.cluster;" ::: "memory"); }
__device__ __forceinline__ void mbar_expect(uint32_t a, uint32_t tx) { asm volatile("mbarrier.arrive.expect_tx.shared::cta.b64 _, [%0], %1;" ::"r"(a), "r"(tx) : "memory"); }
__device__ __forceinline__ void mbar_arrive(uint32_t a) { asm volatile("mbarrier.arrive.shared::cta.b64 _, [%0];" ::"r"(a) : "memory"); }
__device__ __forceinline__ void mbar_wait(uint32_t a, uint32_t parity = 0) {
    uint32_t ok, n = 0;
    do {
        asm volatile("{.reg .pred p; mbarrier.try_wait.parity.shared::cta.b64 p, [%1], %2; selp.u32 %0, 1, 0, p;}" : "=r"(ok) : "r"(a), "r"(parity) : "memory");
    } while (!ok && ++n < SPIN_LIMIT);
}
__device__ __forceinline__ void mbar_wait_cluster(uint32_t a, uint32_t parity = 0) {
    uint32_t ok, n = 0;
    do {
        asm volatile("{.reg .pred p; mbarrier.try_wait.parity.acquire.cluster.shared::cta.b64 p, [%1], %2; selp.u32 %0, 1, 0, p;}" : "=r"(ok) : "r"(a), "r"(parity) : "memory");
    } while (!ok && ++n < SPIN_LIMIT);
}
__device__ __forceinline__ uint32_t mbar_test(uint32_t a, uint32_t parity) {
    uint32_t ok;
    asm volatile("{.reg .pred p; mbarrier.test_wait.parity.shared::cta.b64 p, [%1], %2; selp.u32 %0, 1, 0, p;}" : "=r"(ok) : "r"(a), "r"(parity) : "memory");
    return ok;
}
__device__ __forceinline__ uint32_t mapa(uint32_t a, uint32_t rank) { uint32_t r; asm("mapa.shared::cluster.u32 %0, %1, %2;" : "=r"(r) : "r"(a), "r"(rank)); return r; }
__device__ __forceinline__ void st_async2(uint32_t a, float x, float y, uint32_t mbar) {
    asm volatile("st.async.weak.shared::cluster.mbarrier::complete_tx::bytes.v2.f32 [%0], {%1,%2}, [%3];" ::"r"(a), "f"(x), "f"(y), "r"(mbar) : "memory");
}
__device__ __forceinline__ void st_async2u(uint32_t a, uint32_t x, uint32_t y, uint32_t mbar) {
    asm volatile("st.async.weak.shared::cluster.mbarrier::complete_tx::bytes.v2.b32 [%0], {%1,%2}, [%3];" ::"r"(a), "r"(x), "r"(y), "r"(mbar) : "memory");
}
__device__ __forceinline__ void cluster_arrive() { asm volatile("barrier.cluster.arrive.relaxed.aligned;" ::: "memory"); }
__device__ __forceinline__ void cluster_wait() { asm volatile("barrier.cluster.wait.acquire.aligned;" ::: "memory"); }
__device__ __forceinline__ void bulk_g2s(uint32_t dst, const void* src, uint32_t bytes, uint32_t mbar) {
    asm volatile("cp.async.bulk.shared::cluster.global.mbarrier::complete_tx::bytes [%0], [%1], %2, [%3];" ::"r"(dst), "l"(src), "r"(bytes), "r"(mbar) : "memory");
}
__device__ __forceinline__ void tma2d(uint32_t dst, const CUtensorMap* map, int c0, int c1, uint32_t mbar) {
    asm volatile("cp.async.bulk.tensor.2d.shared::cluster.global.mbarrier::complete_tx::bytes.L2::cache_hint [%0], [%1, {%3, %4}], [%2], %5;"
                 ::"r"(dst), "l"(map), "r"(mbar), "r"(c0), "r"(c1), "l"(0x12F0000000000000ull) : "memory");
}
__device__ __forceinline__ void ldsm4(uint32_t (&a)[4], uint32_t addr) {
    asm volatile("ldmatrix.sync.aligned.m8n8.x4.shared.b16 {%0,%1,%2,%3}, [%4];" : "=r"(a[0]), "=r"(a[1]), "=r"(a[2]), "=r"(a[3]) : "r"(addr) : "memory");
}
__device__ __forceinline__ void ldsm4t(uint32_t (&a)[4], uint32_t addr) {
    asm volatile("ldmatrix.sync.aligned.m8n8.x4.trans.shared.b16 {%0,%1,%2,%3}, [%4];" : "=r"(a[0]), "=r"(a[1]), "=r"(a[2]), "=r"(a[3]) : "r"(addr) : "memory");
}
__device__ __forceinline__ void mma16816(float (&c)[4], const uint32_t (&a)[4], uint32_t b0, uint32_t b1) {
    asm volatile("mma.sync.aligned.m16n8k16.row.col.f32.bf16.bf16.f32 {%0,%1,%2,%3}, {%4,%5,%6,%7}, {%8,%9}, {%0,%1,%2,%3};"
                 : "+f"(c[0]), "+f"(c[1]), "+f"(c[2]), "+f"(c[3]) : "r"(a[0]), "r"(a[1]), "r"(a[2]), "r"(a[3]), "r"(b0), "r"(b1));
}
__device__ __forceinline__ uint32_t lds32(uint32_t a) { uint32_t v; asm volatile("ld.shared.u32 %0, [%1];" : "=r"(v) : "r"(a) : "memory"); return v; }
__device__ __forceinline__ float ldsf(uint32_t a) { float v; asm volatile("ld.shared.f32 %0, [%1];" : "=f"(v) : "r"(a) : "memory"); return v; }
__device__ __forceinline__ uint2 lds64(uint32_t a) { uint2 v; asm volatile("ld.shared.v2.u32 {%0,%1}, [%2];" : "=r"(v.x), "=r"(v.y) : "r"(a) : "memory"); return v; }
__device__ __forceinline__ uint4 lds128(uint32_t a) { uint4 v; asm volatile("ld.shared.v4.u32 {%0,%1,%2,%3}, [%4];" : "=r"(v.x), "=r"(v.y), "=r"(v.z), "=r"(v.w) : "r"(a) : "memory"); return v; }
__device__ __forceinline__ void sts128(uint32_t a, const uint4& v) { asm volatile("st.shared.v4.u32 [%0], {%1,%2,%3,%4};" ::"r"(a), "r"(v.x), "r"(v.y), "r"(v.z), "r"(v.w) : "memory"); }
__device__ __forceinline__ void named_bar(int id, int n) { asm volatile("bar.sync %0, %1;" ::"r"(id), "r"(n) : "memory"); }
__device__ __forceinline__ float bf_lo(uint32_t u) { return __uint_as_float(u << 16); }
__device__ __forceinline__ float bf_hi(uint32_t u) { return __uint_as_float(u & 0xffff0000u); }
__device__ __forceinline__ float rbf(float f) { uint32_t u; asm("cvt.rn.bf16x2.f32 %0, %1, %2;" : "=r"(u) : "f"(f), "f"(0.f)); return __uint_as_float(u); }
__device__ __forceinline__ uint32_t pack_bf(float lo, float hi) { __nv_bfloat162 v = __floats2bfloat162_rn(lo, hi); return *reinterpret_cast<uint32_t*>(&v); }
__device__ __forceinline__ uint32_t encu(uint32_t u) { return u == 0u ? 0x80000000u : u; }
__device__ __forceinline__ uint32_t enc(float f) { return encu(__float_as_uint(f)); }
__device__ __forceinline__ bool full4(const uint4& v) { return v.x && v.y && v.z && v.w; }
__device__ __forceinline__ void st_relaxed1(uint32_t* p, uint32_t a) { asm volatile("st.relaxed.gpu.global.u32 [%0], %1;" ::"l"(p), "r"(a) : "memory"); }
__device__ __forceinline__ void st_relaxed2(uint32_t* p, uint32_t a, uint32_t b) { asm volatile("st.relaxed.gpu.global.v2.u32 [%0], {%1,%2};" ::"l"(p), "r"(a), "r"(b) : "memory"); }
__device__ __forceinline__ void st_relaxed4(uint32_t* p, uint32_t a, uint32_t b, uint32_t c, uint32_t d) { asm volatile("st.relaxed.gpu.global.v4.u32 [%0], {%1,%2,%3,%4};" ::"l"(p), "r"(a), "r"(b), "r"(c), "r"(d) : "memory"); }
__device__ __forceinline__ void ld_relaxed4_if(uint4& v, const uint32_t* p, uint32_t c) {
    asm volatile("{.reg .pred p; setp.ne.u32 p, %5, 0; @p ld.relaxed.gpu.global.v4.u32 {%0,%1,%2,%3}, [%4];}"
                 : "+r"(v.x), "+r"(v.y), "+r"(v.z), "+r"(v.w) : "l"(p), "r"(c) : "memory");
}
__device__ __forceinline__ float gelu_tanh(float g) { return __fdividef(g, 1.f + __expf(-1.5957691216057308f * (g + 0.044715f * g * g * g))); }

__device__ __forceinline__ int slot_of(int i) { return i >= 2 * NSLOT ? i - 2 * NSLOT : (i >= NSLOT ? i - NSLOT : i); }
__device__ __forceinline__ uint32_t bidx(int i) { return i < KC ? B_CP : slot_of(i); }
__device__ __forceinline__ uint32_t bpar(int i) { return i >= NSLOT + KC && !(i >= 2 * NSLOT + KC); }

__device__ __forceinline__ uint32_t fpos(uint32_t w) { return ((w & 3) << 3) | ((w >> 3) << 1) | ((w >> 2) & 1); }

__device__ __noinline__ float2 rows(int first, int n, int par, uint32_t sb, uint32_t offT, uint32_t frag, uint32_t barv, uint32_t vstep) {
    float c0[4] = {0.f, 0.f, 0.f, 0.f}, c1[4] = {0.f, 0.f, 0.f, 0.f};
    const uint32_t bar = sb + SM_BAR;
#pragma unroll 1
    for (int j = par; j < n; j += 2) {
        const int i = first + j;
        const uint32_t ta = sb + slot_of(i) * TILE + offT, bt = bar + 8 * bidx(i), pt = bpar(i);
        uint32_t ok, cnt = 0;
        do {
            asm volatile("{.reg .pred p, q; mbarrier.try_wait.parity.shared::cta.b64 p, [%1], 0; mbarrier.try_wait.parity.shared::cta.b64 q, [%2], %3;"
                         " and.pred p, p, q; selp.u32 %0, 1, 0, p;}" : "=r"(ok) : "r"(barv + j * vstep), "r"(bt), "r"(pt), "r"(ta) : "memory");
        } while (!ok && ++cnt < SPIN_LIMIT);
        const uint4 b0 = lds128(frag + j * 128), b1 = lds128(frag + j * 128 + 16);
        uint32_t a[4][4];
#pragma unroll
        for (int kb = 0; kb < 4; kb++) ldsm4t(a[kb], ta + kb * 2048);
        mma16816(c0, a[0], b0.x, b0.y); mma16816(c1, a[1], b0.z, b0.w);
        mma16816(c0, a[2], b1.x, b1.y); mma16816(c1, a[3], b1.z, b1.w);
    }
    return make_float2(c0[0] + c1[0], c0[2] + c1[2]);
}

__device__ __forceinline__ uint32_t gtime() { uint32_t t; asm volatile("mov.u32 %0, %%globaltimer_lo;" : "=r"(t)); return t; }
__device__ __noinline__ void poll_slices(uint32_t* in, uint32_t dst, uint32_t barv, int lane, uint32_t t0, int nsl, uint32_t hm, uint32_t due1, uint32_t due2) {
    in += lane * 4;
    dst += lane * 16;
    barv += (lane >> 3) * 8;
    uint4 v[NL];
    uint32_t pend = 0, n = 0;
#pragma unroll
    for (int k = 0; k < NL; k++) { v[k] = make_uint4(0u, 0u, 0u, 0u); if (k * 4 + (lane >> 3) < nsl) pend |= 1u << k; }
    while (__any_sync(0xffffffffu, pend) && ++n < SPIN_LIMIT) {
#pragma unroll
        for (int k = 0; k < NL; k++) ld_relaxed4_if(v[k], in + k * 128, pend & (1u << k));
#pragma unroll
        for (int k = 0; k < NL; k++)
            if ((pend & (1u << k)) && full4(v[k])) {
                sts128(dst + k * 512, v[k]);
                mbar_arrive(barv + k * 32);
                st_relaxed4(in + k * 128, 0u, 0u, 0u, 0u);
                pend &= ~(1u << k);
            }
        const uint32_t due = __any_sync(0xffffffffu, pend & hm) ? due1 : due2;
        const uint32_t t1 = gtime() - t0;
        if (t1 < due) {
            const uint32_t until = min(due, t1 + SLOWP);
#pragma unroll 1
            for (int k = 0; k < 64 && gtime() - t0 < until; k++) __nanosleep(100);
        }
    }
}

__global__ void __launch_bounds__(NTHR, 1)
fused_decode_kernel(const __nv_bfloat16* __restrict__ wq, const __nv_bfloat16* __restrict__ wg, const __nv_bfloat16* __restrict__ x,
                    const __nv_bfloat16* __restrict__ gate_w, __nv_bfloat16* __restrict__ out, const __grid_constant__ Maps maps) {
    extern __shared__ unsigned char sm_raw[];
    const uint32_t sb = (smem_u32(sm_raw) + 1023u) & ~1023u;
    unsigned char* sm = sm_raw + (sb - smem_u32(sm_raw));
    {
        uint32_t b0, t0_;
        asm volatile("mov.u32 %0, %%ctaid.x;" : "=r"(b0));
        asm volatile("mov.u32 %0, %%tid.x;" : "=r"(t0_));
        if (t0_ < 256) {
            const uint32_t row = t0_ >> 3, ch = t0_ & 7, q = b0 >> 2;
            const uint32_t dst = sb + row * 128 + ((ch ^ (row & 7)) << 4);
            if ((b0 & 3) == 3 && b0 < 4 * NFFN) {
                const char* src = reinterpret_cast<const char*>(wg) + (row * (DF * 2) + q * 128 + ch * 16);
#pragma unroll
                for (int k = 0; k < 2 * KC; k++)
                    asm volatile("cp.async.cg.shared.global [%0], [%1], 16;" ::"r"(dst + k * 4096), "l"(src + k * 32 * (DF * 2)) : "memory");
            } else {
                const uint32_t c = (~b0 & 3) ? b0 - q : q + (NATT - 6 - NFFN);
                const char* src = reinterpret_cast<const char*>(wq) + (row * (NH * DH * 2) + c * 128 + ch * 16);
#pragma unroll
                for (int k = 0; k < 2 * KC; k++)
                    asm volatile("cp.async.cg.shared.global [%0], [%1], 16;" ::"r"(dst + k * 4096), "l"(src + k * 32 * (NH * DH * 2)) : "memory");
            }
        }
    }
    uint32_t bid;
    int tid;
    asm volatile("mov.u32 %0, %%ctaid.x;" : "=r"(bid));
    asm volatile("mov.u32 %0, %%tid.x;" : "=r"(tid));
    const int lane = tid & 31;
    const int warp = __shfl_sync(0xffffffffu, tid >> 5, 0);
    const uint32_t q4 = bid >> 2, r4 = bid & 3;
    const bool loc = r4 != 3;
    const bool att = loc || q4 >= NFFN;
    const uint32_t col = loc ? 3 * q4 + r4 : (q4 < NFFN ? q4 : q4 + (NATT - 6 - NFFN));
    const int cl = bid >> 3, rk = bid & 7;
    const bool own = cl < NOWN;
    const int b = att ? col : NATT + col;
    float* s_part = reinterpret_cast<float*>(sm + SM_PART);
    float* s_red = reinterpret_cast<float*>(sm + SM_RED);
    const uint32_t bar = sb + SM_BAR, bar_empty = bar + 8 * B_EMPTY;
    const int n1 = att ? 42 : (own ? 32 : 20);
    const int nitems = own ? n1 + (att ? NBA : NBF) : n1;

    if (warp >= 8) {
        const int W = att ? WATT : (own ? WFFN : WFN), W2 = att ? WA2 : W;
        const int B = att ? BA : BF;
        uint32_t t0;
        asm volatile("mov.u32 %0, %%globaltimer_lo;" : "=r"(t0));
        const int h = b / 3, r = b - 3 * h, f = b - NATT;
        const int kvrow = h * SK + (SK - WIN);
        if (lane == 0) {
            const CUtensorMap* m0 = &maps.m[att ? 0 : 4];
            const int c0 = (att ? b : f) * 64;
#pragma unroll
            for (int k = 0; k < WMAX / 2; k++) {
                const int i = (2 * k + (warp - 8) + KC) % WMAX;
                mbar_init(bar + 8 * i, 1);
                mbar_fence_init();
                if (i >= KC && i < B) {
                    mbar_expect(bar + 8 * i, TILE);
                    tma2d(sb + i * TILE, m0, c0, i * 64, bar + 8 * i);
                }
            }
        }
        __syncwarp();
        uint32_t xw[10];
        if (warp == 9) {
#pragma unroll
            for (int k = 0; k < 10; k++) xw[k] = __ldg(reinterpret_cast<const uint32_t*>(x) + k * 32 + lane);
        }
        named_bar(0, NTHR);
        cluster_arrive();
        if (warp == 9) {
#pragma unroll
            for (int k = 0; k < 10; k++) reinterpret_cast<uint32_t*>(sm + SM_X)[k * 32 + fpos(lane)] = xw[k];
            __syncwarp();
            if (lane == 0) mbar_arrive(bar + 8 * B_X);
            if (lane < 3) asm volatile("prefetch.tensormap [%0];" ::"l"(&maps.m[lane == 2 ? 3 : (att ? 1 : 5) + lane]) : "memory");
        }
        if (warp == 8) {
            const int t2 = att ? 26 : 20;
            const CUtensorMap* mpa = &maps.m[att ? 0 : 4];
            const CUtensorMap* mpd = &maps.m[3];
            const int ca = (att ? b : f) * 64, cb = att ? r * 64 : ca, cc = att ? r * 64 : cl * 64, cd = cl * 64;
            const int rb = att ? kvrow - 640 : -640, rc = att ? kvrow - 26 * 64 : (rk >> 2) * 64 - 20 * 128;
            const int rd = ((att ? rk - (rk >> 2) : 6 * ND + 6 + (rk >> 2)) - 6 * n1) * 64, nd = att ? 42 + ND : 32;
            const int stc = att ? 64 : 128;
            const int nl = att ? 42 : (own ? NFE : 64);
            const uint32_t sa = att ? DA : (own ? DF_ : DN), sl = att ? DL - (GAP + NBA - 1) / NBA : DFL, gap = att ? GAP : 0;
            uint32_t n = 0;
#pragma unroll
            for (int rd_ = 0; rd_ < 2; rd_++) {
                const int i = B + 32 * rd_ + lane;
                const uint32_t due = TOFF + t0 + (i < nl ? (i - B + 1) * sa : (nl - B) * sa + gap + (i - nl + 1) * sl);
                const bool p1 = i >= 10, p2 = i >= t2, p3 = i >= n1;
                const CUtensorMap* mp = p3 ? mpd : mpa + (p1 ? 1 : 0) + (p2 ? 1 : 0);
                const int c0 = p3 ? cd : (p2 ? cc : (p1 ? cb : ca));
                const int c1 = (p3 ? rd + max(i - nd, 0) * 128 : (p2 ? rc : (p1 ? rb : 0))) + i * (p3 ? 384 : (p2 ? stc : 64));
                const int slot = slot_of(i);
                const int iw = i - (p3 ? W2 : W);
                const bool he = i == 26 || i == 36 || (att && (i == 42 || i == 52));
                const uint32_t wa = bar + 8 * bidx(max(iw, 0)), wpar = bpar(iw);
                const uint32_t eb = bar_empty + (i == 26 ? 0 : (i == 36 ? 8 : (i == 42 ? 16 : 24)));
                const uint32_t br = bar + 8 * slot, dst = sb + slot * TILE;
                const int lw = iw >= 0 ? lane : -1, le = he ? lane : -1;
                asm volatile("" ::"r"(due), "l"(mp), "r"(c0), "r"(c1), "r"(wa), "r"(wpar), "r"(eb), "r"(br), "r"(dst), "r"(lw), "r"(le));
                const int cnt = min(32, nitems - B - 32 * rd_);
#pragma unroll 1
                for (int k = 0; k < cnt; k++) {
                    uint32_t bad;
                    asm volatile("{.reg .pred p, q, r, pw, pe; setp.eq.u32 p, %1, %2; setp.eq.u32 pw, %7, %2; setp.eq.u32 pe, %8, %2; setp.ne.u32 q, %7, %2; setp.ne.u32 r, %8, %2;"
                                 " @pw mbarrier.test_wait.parity.shared::cta.b64 q, [%3], %4;"
                                 " @pe mbarrier.test_wait.parity.shared::cta.b64 r, [%5], 0;"
                                 " @p mbarrier.arrive.expect_tx.shared::cta.b64 _, [%6], 8192;"
                                 " and.pred q, q, r; selp.u32 %0, 0, 1, q;}"
                                 : "=r"(bad) : "r"(lane), "r"(k), "r"(wa), "r"(wpar), "r"(eb), "r"(br), "r"(lw), "r"(le) : "memory");
                    const uint32_t du = __shfl_sync(0xffffffffu, due, k);
                    while ((int)(gtime() - du) < 0 && ++n < SPIN_LIMIT * 8) {}
                    if (lane == k) {
                        if (bad) { if (iw >= 0) mbar_wait(wa, wpar); if (he) mbar_wait(eb); }
                        tma2d(dst, mp, c0, c1, br);
                    }
                    __syncwarp();
                }
            }
        }
        else if (own) {
            poll_slices(g_v + (size_t)bid * RS * 32, sb + SM_VEC, bar + 8 * B_VEC, lane, t0, att ? NBA : NB + NBF, att ? 0u : 7u, (20 - BF) * DF_ + DUEH, (42 - BA) * DA + DUEO);
            __syncwarp();
        }
        return;
    }

    const int par = warp >> 2, mb = warp & 3, g = lane >> 2, t = lane & 3;
    const uint32_t offT = (lane & 7) * 128 + (lane >> 4) * 1024 + (((2 * mb + ((lane >> 3) & 1)) ^ (lane & 7)) << 4);
    uint32_t sbo;
    asm volatile("mov.u32 %0, %1;" : "=r"(sbo) : "r"(sb));
    const uint32_t xfrag = sb + SM_X + t * 32;
    if (lane == 0) {
        if (warp == 0) mbar_init(bar + 8 * B_CP, 256);
        else {
#pragma unroll
            for (int k = 0; k < 8; k++) mbar_init(bar + 64 * warp + 8 * k, warp < 4 ? 1 : 8);
        }
        mbar_fence_init();
        if (warp == 3) {
            mbar_expect(bar + 8 * B_SC, loc ? 3 * 4096 : 4096);
            mbar_expect(bar + 8 * B_FINA, 16 * 256);
            mbar_expect(bar + 8 * B_FINB, 4 * 256);
        }
    }
    __syncwarp();
    named_bar(0, NTHR);
    cluster_arrive();
    asm volatile("cp.async.mbarrier.arrive.noinc.shared::cta.b64 [%0];" ::"r"(bar + 8 * B_CP) : "memory");
    const int h = b / 3, r = b - 3 * h;
    const uint32_t fin_row = mapa(sb + SM_FIN + (mb * 16 + g * 2) * 4, LEAD), fin_bar = mapa(bar + 8 * B_FINA, LEAD);
    const int pw = lane * 2;
    uint32_t pslot;
    {
        const int u = b - 6 * ND, a6 = u < 0 ? b % 6 : u & 7, j = u < 0 ? b / 6 : (u >> 3);
        if (!att) pslot = ((col & 1) * 4 + 3) * RS + (col >> 1);
        else if (a6 < 6) pslot = (a6 + (a6 >= 3)) * RS + j + (u < 0 ? 0 : ND);
        else pslot = ((a6 - 6) * 4 + 3) * RS + NB + j;
    }
    uint32_t* pub = g_v + ((size_t)warp * CS * RS + pslot) * 32 + fpos(lane);

    if (!att) {
        float ga = 0.f, gf = 0.f;
        if (rk == LEAD && own) {
            float s = 0.f;
#pragma unroll
            for (int i = 0; i < 5; i++) {
                const uint2 gx = __ldg(reinterpret_cast<const uint2*>(x) + i * 32 + lane);
                const uint2 gw = __ldg(reinterpret_cast<const uint2*>(gate_w) + i * 32 + lane);
                s += rbf(bf_lo(gx.x) * bf_lo(gw.x)); s += rbf(bf_hi(gx.x) * bf_hi(gw.x));
                s += rbf(bf_lo(gx.y) * bf_lo(gw.y)); s += rbf(bf_hi(gx.y) * bf_hi(gw.y));
            }
#pragma unroll
            for (int o = 16; o; o >>= 1) s += __shfl_xor_sync(0xffffffffu, s, o);
            ga = rbf(1.f / (1.f + __expf(-rbf(s))));
            gf = rbf(1.f - ga);
        }
        float2 y = rows(0, 10, par, sbo, offT, xfrag, bar + 8 * B_X, 0);
        if (lane == 0) mbar_arrive(bar_empty);
        if (t == 0) { s_part[par * 64 + mb * 16 + g] = y.x; s_part[par * 64 + mb * 16 + g + 8] = y.y; }
        y = rows(10, 10, par, sbo, offT, xfrag, bar + 8 * B_X, 0);
        if (lane == 0) mbar_arrive(bar_empty + 8);
        if (t == 0) { s_part[128 + par * 64 + mb * 16 + g] = y.x; s_part[128 + par * 64 + mb * 16 + g + 8] = y.y; }
        named_bar(1, 256);
        {
            const float2 g0 = *reinterpret_cast<const float2*>(s_part + pw), g1 = *reinterpret_cast<const float2*>(s_part + 64 + pw);
            const float2 u0 = *reinterpret_cast<const float2*>(s_part + 128 + pw), u1 = *reinterpret_cast<const float2*>(s_part + 192 + pw);
            const uint32_t w = encu(pack_bf(rbf(gelu_tanh(rbf(g0.x + g1.x))) * rbf(u0.x + u1.x), rbf(gelu_tanh(rbf(g0.y + g1.y))) * rbf(u0.y + u1.y)));
            st_relaxed1(pub, w);
            if (warp < NOWN - 8) st_relaxed1(pub + 8 * CS * RS * 32, w);
        }
        if (!own) return;
        cluster_wait();
        float zb = 0.f;
        const uint32_t fin = sb + SM_FIN + tid * 4;
        __nv_bfloat16* op = out + cl * 64 + (tid & 48) + ((tid & 15) >> 1) + ((tid & 1) << 3);
#pragma unroll 1
        for (int ps = 0; ps < 2; ps++) {
            const uint32_t dst = fin_row + (ps ? rk * 2 + par : 16 + (rk >> 2) * 2 + par) * 288, dbar = fin_bar + (ps ? 0 : 8);
            const uint32_t fa = fin + (ps ? 0 : 16 * 288), fb = bar + 8 * (ps ? B_FINA : B_FINB);
            asm volatile("" ::"r"(dst), "r"(dbar), "r"(fa), "r"(fb));
            y = rows(20 + NB * ps, ps ? NBF : NB, par, sbo, offT, sb + SM_VEC + ps * NB * 128 + t * 32, bar + 8 * (B_VEC + NB * ps), 8);
            if (t == 0) st_async2(dst, y.x, y.y, dbar);
            if (rk == LEAD && tid < 64) {
                mbar_wait_cluster(fb);
                float v[16];
#pragma unroll
                for (int k = 0; k < 16; k++) v[k] = ldsf(fa + k * 288);
                const float s0 = (v[0] + v[1]) + (v[2] + v[3]), s1 = (v[4] + v[5]) + (v[6] + v[7]);
                const float s2 = (v[8] + v[9]) + (v[10] + v[11]), s3 = (v[12] + v[13]) + (v[14] + v[15]);
                const float s = ps ? (s0 + s1) + (s2 + s3) : s0;
                const float z = rbf((ps ? ga : gf) * rbf(s));
                if (ps) *op = __float2bfloat16_rn(z + zb);
                zb = z;
            }
        }
        return;
    }

    uint32_t bv[8];
    {
        const float2 y = rows(0, 10, par, sbo, offT, xfrag, bar + 8 * B_X, 0);
        if (lane == 0) mbar_arrive(bar_empty);
        if (t == 0) { s_part[par * 64 + mb * 16 + g] = y.x; s_part[par * 64 + mb * 16 + g + 8] = y.y; }
        named_bar(1, 256);
#pragma unroll
        for (int j = 0; j < 8; j++) {
            const int c = j * 8 + 2 * t;
            const float2 u0 = *reinterpret_cast<const float2*>(s_part + c), u1 = *reinterpret_cast<const float2*>(s_part + 64 + c);
            bv[j] = pack_bf(u0.x + u1.x, u0.y + u1.y);
        }
    }
    cluster_wait();
    {
        const uint32_t offN = (mb * 16 + (lane & 7) + (((lane >> 3) & 1) << 3)) * 128 + (((lane >> 4) ^ (lane & 7)) << 4);
        const int pr = r + t >= 3 ? r + t - 3 : r + t;
        const uint32_t prk = loc ? (rk & 4) + pr : rk;
        const uint32_t sdst = mapa(sb + SM_SC + r * 4096 + (mb * 16 + g * 2) * 4, prk), sbar = mapa(bar + 8 * B_SC, prk);
        uint32_t* dst = g_s + ((size_t)((h & 1) * 3 + pr) * 3 + r) * WIN + mb * 16 + g * 2;
        const int how = t == 0 || (loc && t < 3) ? 1 : (t < 3 ? 2 : 0);
#pragma unroll 1
        for (int j = par; j < 16; j += 2) {
            const int i = 10 + j;
            const uint32_t ta = sb + i * TILE + offN;
            mbar_wait(bar + 8 * i);
            uint32_t a[4][4];
#pragma unroll
            for (int kb = 0; kb < 4; kb++) ldsm4(a[kb], ta ^ (kb << 5));
            float c0[4] = {0.f, 0.f, 0.f, 0.f}, c1[4] = {0.f, 0.f, 0.f, 0.f};
            mma16816(c0, a[0], bv[0], bv[1]); mma16816(c1, a[1], bv[2], bv[3]);
            mma16816(c0, a[2], bv[4], bv[5]); mma16816(c1, a[3], bv[6], bv[7]);
            const uint32_t lo = enc(c0[0] + c1[0]), hi = enc(c0[2] + c1[2]);
            if (how == 1) st_async2u(sdst + j * 256, lo, hi, sbar);
            if (how == 2) st_relaxed2(dst + j * 64, lo, hi);
            if (lane == 0 && (j == 4 + par || j == 14 + par)) mbar_arrive(bar_empty + (j < 6 ? 8 : 16));
        }
    }
    {
        const uint32_t sc = sb + SM_SC + tid * 16;
        if (!loc) {
            const int ra = r == 0 ? 1 : 0, rc = r == 2 ? 1 : 2;
            uint32_t* ma = g_s + ((size_t)(b - (NATT - 6)) * 3 + ra) * WIN + tid * 4;
            uint32_t* mc = g_s + ((size_t)(b - (NATT - 6)) * 3 + rc) * WIN + tid * 4;
            uint4 pa = make_uint4(0u, 0u, 0u, 0u), pc = pa;
            uint32_t n = 0, pend = 3u;
            while (pend && ++n < SPIN_LIMIT) {
                ld_relaxed4_if(pa, ma, pend & 1u); ld_relaxed4_if(pc, mc, pend & 2u);
                pend = (full4(pa) ? 0u : 1u) | (full4(pc) ? 0u : 2u);
            }
            sts128(sc + ra * 4096, pa);
            sts128(sc + rc * 4096, pc);
            st_relaxed4(ma, 0u, 0u, 0u, 0u);
            st_relaxed4(mc, 0u, 0u, 0u, 0u);
        }
        mbar_wait_cluster(bar + 8 * B_SC);
        const uint4 p0 = lds128(sc), p1 = lds128(sc + 4096), p2 = lds128(sc + 8192);
        float s[4];
        s[0] = (__uint_as_float(p0.x) + __uint_as_float(p1.x)) + __uint_as_float(p2.x);
        s[1] = (__uint_as_float(p0.y) + __uint_as_float(p1.y)) + __uint_as_float(p2.y);
        s[2] = (__uint_as_float(p0.z) + __uint_as_float(p1.z)) + __uint_as_float(p2.z);
        s[3] = (__uint_as_float(p0.w) + __uint_as_float(p1.w)) + __uint_as_float(p2.w);
        float m = -INFINITY;
#pragma unroll
        for (int k = 0; k < 4; k++) {
            s[k] = rbf(rbf(s[k]) * 0.07216878364870322f);
            m = fmaxf(m, s[k]);
        }
#pragma unroll
        for (int o = 16; o; o >>= 1) m = fmaxf(m, __shfl_xor_sync(0xffffffffu, m, o));
        if (lane == 0) s_red[warp] = m;
        named_bar(1, 256);
        {
            const float4 m0 = *reinterpret_cast<const float4*>(s_red), m1 = *reinterpret_cast<const float4*>(s_red + 4);
            m = fmaxf(fmaxf(fmaxf(m0.x, m0.y), fmaxf(m0.z, m0.w)), fmaxf(fmaxf(m1.x, m1.y), fmaxf(m1.z, m1.w)));
        }
        float l = 0.f;
#pragma unroll
        for (int k = 0; k < 4; k++) { s[k] = __expf(s[k] - m); l += s[k]; }
#pragma unroll
        for (int o = 16; o; o >>= 1) l += __shfl_xor_sync(0xffffffffu, l, o);
        if (lane == 0) s_red[8 + warp] = l;
        named_bar(1, 256);
        {
            const float4 l0 = *reinterpret_cast<const float4*>(s_red + 8), l1 = *reinterpret_cast<const float4*>(s_red + 12);
            l = ((l0.x + l0.y) + (l0.z + l0.w)) + ((l1.x + l1.y) + (l1.z + l1.w));
        }
        const float inv = 1.f / l;
        reinterpret_cast<uint2*>(sm + SM_P)[(tid >> 4) * 16 + t * 4 + ((tid >> 2) & 3)] = make_uint2(pack_bf(s[0] * inv, s[2] * inv), pack_bf(s[1] * inv, s[3] * inv));
        named_bar(1, 256);
    }
    {
        const float2 y = rows(26, 16, par, sbo, offT, sb + SM_P + t * 32, bar + 8 * B_X, 0);
        if (lane == 0) mbar_arrive(bar_empty + 24);
        if (t == 0) { s_part[par * 64 + mb * 16 + g] = y.x; s_part[par * 64 + mb * 16 + g + 8] = y.y; }
        named_bar(1, 256);
        const float2 u0 = *reinterpret_cast<const float2*>(s_part + pw), u1 = *reinterpret_cast<const float2*>(s_part + 64 + pw);
        const uint32_t w = encu(pack_bf(u0.x + u1.x, u0.y + u1.y));
        st_relaxed1(pub, w);
        if (warp < NOWN - 8) st_relaxed1(pub + 8 * CS * RS * 32, w);
    }
    if (!own) return;
    {
        const uint32_t dst = fin_row + (rk * 2 + par) * 288;
        asm volatile("" ::"r"(dst), "r"(fin_bar));
        const float2 y = rows(42, NBA, par, sbo, offT, sb + SM_VEC + t * 32, bar + 8 * B_VEC, 8);
        if (t == 0) st_async2(dst, y.x, y.y, fin_bar);
    }
}

namespace plain {

constexpr int NSPARE = 12, NCTA = NSRC + NSPARE, NBLK = 40;
constexpr int FULLP = 8, PH1SLEEP = 100;
constexpr int WATT = 8, WFFN = 4;
constexpr int ATT_ITEMS = 52, FFN_ITEMS = 30;
constexpr int SM_BAR = SM_RED + 128;
constexpr int NBAR = NSLOT + 5;
constexpr int SM_TOTAL = SM_BAR + NBAR * 8 + 1024;
__device__ __align__(128) uint32_t g_s[NATT * 3 * WIN];

__device__ __align__(128) uint32_t g_f[NBLK * NSRC * 16];

__device__ __forceinline__ uint32_t opaque(uint32_t v) { uint32_t r; asm volatile("mov.u32 %0, %1;" : "=r"(r) : "r"(v)); return r; }

__device__ __forceinline__ void rows_x(int first, int par, uint32_t sb, uint32_t offT, uint32_t xfrag, uint32_t bar_full, float& lo, float& hi) {
    float c0[4] = {0.f, 0.f, 0.f, 0.f}, c1[4] = {0.f, 0.f, 0.f, 0.f};
#pragma unroll 1
    for (int j = par; j < 10; j += 2) {
        const int i = first + j;
        uint32_t bx[8];
#pragma unroll
        for (int kb = 0; kb < 4; kb++) { bx[2 * kb] = lds32(xfrag + j * 128 + kb * 32); bx[2 * kb + 1] = lds32(xfrag + j * 128 + kb * 32 + 16); }
        mbar_wait(bar_full + 8 * (i < KC ? NSLOT + 4 : i));
        uint32_t a[4][4];
#pragma unroll
        for (int kb = 0; kb < 4; kb++) ldsm4t(a[kb], sb + i * TILE + offT + kb * 2048);
        mma16816(c0, a[0], bx[0], bx[1]); mma16816(c1, a[1], bx[2], bx[3]);
        mma16816(c0, a[2], bx[4], bx[5]); mma16816(c1, a[3], bx[6], bx[7]);
    }
    lo = c0[0] + c1[0];
    hi = c0[2] + c1[2];
}

__device__ __forceinline__ void out_tiles(int first, int par, int mb, uint32_t sb, uint32_t offT, const uint32_t (&bv)[8], uint32_t bar_full,
                                          int lane, int b) {
    uint32_t* dst = g_f + ((size_t)mb * NSRC + b) * 16 + (lane >> 2) * 2;
#pragma unroll 1
    for (int j = par; j < 10; j += 2) {
        const int i = first + j;
        const int slot = i >= NSLOT ? i - NSLOT : i;
        const uint32_t ta = sb + slot * TILE + offT;
        mbar_wait(bar_full + 8 * slot, i >= NSLOT + KC);
        uint32_t a[4][4];
#pragma unroll
        for (int kb = 0; kb < 4; kb++) ldsm4t(a[kb], ta + kb * 2048);
        float c0[4] = {0.f, 0.f, 0.f, 0.f}, c1[4] = {0.f, 0.f, 0.f, 0.f};
        mma16816(c0, a[0], bv[0], bv[1]); mma16816(c1, a[1], bv[2], bv[3]);
        mma16816(c0, a[2], bv[4], bv[5]); mma16816(c1, a[3], bv[6], bv[7]);
        if ((lane & 3) == 0) st_relaxed2(dst + (size_t)j * NSRC * 64, enc(c0[0] + c1[0]), enc(c0[2] + c1[2]));
    }
}

__device__ __forceinline__ void reduce_block(int blk, int lane, const __nv_bfloat16* __restrict__ x,
                                             const __nv_bfloat16* __restrict__ gate_w, __nv_bfloat16* __restrict__ out) {
    float s = 0.f;
#pragma unroll
    for (int i = 0; i < 5; i++) {
        const uint2 gx = __ldg(reinterpret_cast<const uint2*>(x) + i * 32 + lane);
        const uint2 gw = __ldg(reinterpret_cast<const uint2*>(gate_w) + i * 32 + lane);
        s += rbf(bf_lo(gx.x) * bf_lo(gw.x)); s += rbf(bf_hi(gx.x) * bf_hi(gw.x));
        s += rbf(bf_lo(gx.y) * bf_lo(gw.y)); s += rbf(bf_hi(gx.y) * bf_hi(gw.y));
    }
#pragma unroll
    for (int o = 16; o; o >>= 1) s += __shfl_xor_sync(0xffffffffu, s, o);
    const float ga = rbf(1.f / (1.f + __expf(-rbf(s)))), gf = rbf(1.f - ga);
    uint32_t* in = g_f + (size_t)blk * NSRC * 16 + lane * 4;
    const bool b4 = lane & 16, b3 = lane & 8, b2 = lane & 4;
    const int pos = (lane & 3) * 4 + ((lane >> 2) & 3);
    __nv_bfloat16* op = out + blk * 16 + (pos >> 1) + ((pos & 1) << 3);
#pragma unroll 1
    for (int pass = 0; pass < 2; pass++) {
        const uint32_t live = opaque(pass);
        uint4 v[15];
#pragma unroll
        for (int k = 0; k < 15; k++) v[k] = make_uint4(0u, 0u, 0u, 0u);
        uint32_t n = 0, pend = live ? 0x7fffu : 0u;
        bool tight = false;
        while (__any_sync(0xffffffffu, pend != 0u) && ++n < SPIN_LIMIT) {
            const uint32_t m = (tight || (n & (FULLP - 1)) == 1) ? pend : (pend & 1u);
#pragma unroll
            for (int k = 0; k < 15; k++) ld_relaxed4_if(v[k], in + k * 128, m & (1u << k));
#pragma unroll
            for (int k = 0; k < 15; k++) pend &= full4(v[k]) ? ~(1u << k) : ~0u;
            if (!tight) {
                tight = __any_sync(0xffffffffu, !(pend & 1u));
                if (!tight) __nanosleep(PH1SLEEP);
            }
        }
#define RSUM(c) ((((__uint_as_float(v[0].c) + __uint_as_float(v[1].c)) + (__uint_as_float(v[2].c) + __uint_as_float(v[3].c))) + \
                 ((__uint_as_float(v[4].c) + __uint_as_float(v[5].c)) + (__uint_as_float(v[6].c) + __uint_as_float(v[7].c)))) + \
                 ((__uint_as_float(v[8].c) + __uint_as_float(v[9].c)) + (__uint_as_float(v[10].c) + __uint_as_float(v[11].c))))
#define FSUM(c) ((__uint_as_float(v[12].c) + __uint_as_float(v[13].c)) + __uint_as_float(v[14].c))
        const float a[4] = {RSUM(x), RSUM(y), RSUM(z), RSUM(w)}, f[4] = {FSUM(x), FSUM(y), FSUM(z), FSUM(w)};
        float t[4];
#pragma unroll
        for (int j = 0; j < 4; j++) t[j] = (b4 ? f[j] : a[j]) + __shfl_xor_sync(0xffffffffu, b4 ? a[j] : f[j], 16);
        const float u0 = (b3 ? t[2] : t[0]) + __shfl_xor_sync(0xffffffffu, b3 ? t[0] : t[2], 8);
        const float u1 = (b3 ? t[3] : t[1]) + __shfl_xor_sync(0xffffffffu, b3 ? t[1] : t[3], 8);
        const float z = rbf((b4 ? gf : ga) * rbf((b2 ? u1 : u0) + __shfl_xor_sync(0xffffffffu, b2 ? u0 : u1, 4)));
        const float zo = __shfl_xor_sync(0xffffffffu, z, 16);
        if (live && !b4) *op = __float2bfloat16_rn(z + zo);
        if (live) {
#pragma unroll
            for (int k = 0; k < 15; k++) st_relaxed4(in + k * 128, 0u, 0u, 0u, 0u);
        }
    }
}

__global__ void __launch_bounds__(NTHR, 1)
plain_decode_kernel(const __nv_bfloat16* __restrict__ wq, const __nv_bfloat16* __restrict__ wg, const __nv_bfloat16* __restrict__ x,
                    const __nv_bfloat16* __restrict__ gate_w, __nv_bfloat16* __restrict__ out, const __grid_constant__ Maps maps) {
    extern __shared__ unsigned char sm_raw[];
    const uint32_t sb = (smem_u32(sm_raw) + 1023u) & ~1023u;
    unsigned char* sm = sm_raw + (sb - smem_u32(sm_raw));
    const int tid = threadIdx.x, lane = tid & 31;
    const int warp = __shfl_sync(0xffffffffu, tid >> 5, 0);
    const int grp = blockIdx.x / 11, kk = blockIdx.x - grp * 11;
    const int b = kk == 10 ? NSRC + grp : (kk == 4 || kk == 9 ? NATT + grp * 2 + (kk == 9) : grp * 8 + kk - (kk > 4));
    if (tid < 256 && b < NSRC) {
        const int row = tid >> 3, ch = tid & 7;
        const int pitch = b < NATT ? NH * DH : DF;
        const __nv_bfloat16* src = (b < NATT ? wq + b * 64 : wg + (b - NATT) * 64) + (size_t)row * pitch + ch * 8;
        const uint32_t dst = sb + row * 128 + ((ch ^ (row & 7)) << 4);
#pragma unroll
        for (int k = 0; k < 2 * KC; k++)
            asm volatile("cp.async.cg.shared.global [%0], [%1], 16;" ::"r"(dst + k * 4096), "l"(src + (size_t)k * 32 * pitch) : "memory");
    }
    float* s_part = reinterpret_cast<float*>(sm + SM_PART);
    float* s_red = reinterpret_cast<float*>(sm + SM_RED);
    const uint32_t bar_full = sb + SM_BAR, bar_empty = bar_full + 8 * NSLOT, bar_x = bar_empty + 8 * 3;

    if (b >= NSRC) {
        const int s = b - NSRC, j = 9 - (s >> 2) - 3 * warp;
        if (j >= 0) reduce_block(j * 4 + (s & 3), lane, x, gate_w, out);
        return;
    }

    const bool att = b < NATT;
    if (warp >= 8) {
        const int nitems = att ? ATT_ITEMS : FFN_ITEMS;
        const int W = att ? WATT : WFFN;
        const int h = b / 3, r = b - 3 * h, f = b - NATT;
        const int kvrow = h * SK + (SK - WIN);
        if (lane == 0) {
            const CUtensorMap* m0 = &maps.m[att ? 0 : 4];
            const int c0 = (att ? b : f) * 64;
#pragma unroll
            for (int k = 0; k < WMAX / 2; k++) {
                const int i = (2 * k + (warp - 8) + KC) % WMAX;
                mbar_init(bar_full + 8 * i, 1);
                mbar_fence_init();
                if (i >= KC && i < W) {
                    mbar_expect(bar_full + 8 * i, TILE);
                    tma2d(sb + i * TILE, m0, c0, i * 64, bar_full + 8 * i);
                }
            }
        }
        __syncwarp();
        named_bar(0, NTHR);
        if (warp == 8) {
            int my = lane, next = W;
            uint32_t n = 0;
            while (next < nitems && ++n < SPIN_LIMIT * 8) {
                uint32_t landed = 0;
                if (lane < W) landed = mbar_test(bar_full + 8 * (my >= NSLOT ? my - NSLOT : (my < KC ? NSLOT + 4 : my)), my >= NSLOT + KC);
                uint32_t m = __ballot_sync(0xffffffffu, landed);
#pragma unroll 1
                while (m && next < nitems) {
                    const int i = next++;
                    if (lane == __ffs(m) - 1) my = i;
                    m &= m - 1;
                    if (lane == 0) {
                        int map, c0, c1;
                        if (att) {
                            if (i < 10) { map = 0; c0 = b * 64; c1 = i * 64; }
                            else if (i < 26) { map = 1; c0 = r * 64; c1 = kvrow + (i - 10) * 64; }
                            else if (i < 42) { map = 2; c0 = r * 64; c1 = kvrow + (i - 26) * 64; }
                            else { map = 3; c0 = (i - 42) * 64; c1 = b * 64; }
                        } else {
                            if (i < 10) { map = 4; c0 = f * 64; c1 = i * 64; }
                            else if (i < 20) { map = 5; c0 = f * 64; c1 = (i - 10) * 64; }
                            else { map = 6; c0 = (i - 20) * 64; c1 = f * 64; }
                        }
                        int slot = i;
                        if (i >= NSLOT) { slot = i - NSLOT; mbar_wait(bar_empty + (slot < 10 ? 0 : (slot < 16 ? 8 : 16))); }
                        mbar_expect(bar_full + 8 * slot, TILE);
                        tma2d(sb + slot * TILE, &maps.m[map], c0, c1, bar_full + 8 * slot);
                    }
                    __syncwarp();
                }
            }
        }
        return;
    }

    const int par = warp >> 2, mb = warp & 3, g = lane >> 2, t = lane & 3;
    const uint32_t offT = (lane & 7) * 128 + (lane >> 4) * 1024 + (((2 * mb + ((lane >> 3) & 1)) ^ (lane & 7)) << 4);
    const uint32_t xfrag = sb + SM_X + t * 4;
    if (lane == 0) {
        if (warp == 0) {
            mbar_init(bar_x, 1);
            mbar_init(bar_x + 8, 256);
            mbar_fence_init();
            mbar_expect(bar_x, 1280);
            bulk_g2s(sb + SM_X, x, 1280, bar_x);
        } else {
            const int i0 = WMAX + (warp - 1) * 3;
#pragma unroll
            for (int k = 0; k < 3; k++) mbar_init(bar_full + 8 * (i0 + k), warp == 7 ? 8 : 1);
            mbar_fence_init();
        }
    }
    __syncwarp();
    named_bar(0, NTHR);
    asm volatile("cp.async.mbarrier.arrive.noinc.shared::cta.b64 [%0];" ::"r"(bar_x + 8) : "memory");
    const int h = b / 3, r = b - 3 * h;
    mbar_wait(bar_x);
    uint32_t bv[8];

    if (!att) {
        float lo, hi;
        rows_x(0, par, sb, offT, xfrag, bar_full, lo, hi);
        if (lane == 0) mbar_arrive(bar_empty);
        if (t == 0) { s_part[par * 64 + mb * 16 + g] = lo; s_part[par * 64 + mb * 16 + g + 8] = hi; }
        rows_x(10, par, sb, offT, xfrag, bar_full, lo, hi);
        if (t == 0) { s_part[128 + par * 64 + mb * 16 + g] = lo; s_part[128 + par * 64 + mb * 16 + g + 8] = hi; }
        named_bar(1, 256);
#pragma unroll
        for (int j = 0; j < 8; j++) {
            const int c = j * 8 + 2 * t;
            const float2 g0 = *reinterpret_cast<const float2*>(s_part + c), g1 = *reinterpret_cast<const float2*>(s_part + 64 + c);
            const float2 u0 = *reinterpret_cast<const float2*>(s_part + 128 + c), u1 = *reinterpret_cast<const float2*>(s_part + 192 + c);
            bv[j] = pack_bf(rbf(gelu_tanh(rbf(g0.x + g1.x))) * rbf(u0.x + u1.x), rbf(gelu_tanh(rbf(g0.y + g1.y))) * rbf(u0.y + u1.y));
        }
        out_tiles(20, par, mb, sb, offT, bv, bar_full, lane, b);
        return;
    }

    {
        float lo, hi;
        rows_x(0, par, sb, offT, xfrag, bar_full, lo, hi);
        if (lane == 0) mbar_arrive(bar_empty);
        if (t == 0) { s_part[par * 64 + mb * 16 + g] = lo; s_part[par * 64 + mb * 16 + g + 8] = hi; }
        named_bar(1, 256);
#pragma unroll
        for (int j = 0; j < 8; j++) {
            const int c = j * 8 + 2 * t;
            const float2 u0 = *reinterpret_cast<const float2*>(s_part + c), u1 = *reinterpret_cast<const float2*>(s_part + 64 + c);
            bv[j] = pack_bf(u0.x + u1.x, u0.y + u1.y);
        }
    }
    {
        const uint32_t offN = (mb * 16 + (lane & 7) + (((lane >> 3) & 1) << 3)) * 128 + (((lane >> 4) ^ (lane & 7)) << 4);
        const int peer = t == 1 ? (r == 2 ? 0 : r + 1) : (r == 0 ? 2 : r - 1);
        uint32_t* dst = g_s + ((size_t)(h * 3 + peer) * 3 + r) * WIN + mb * 16 + g * 2;
        uint2* sdst = reinterpret_cast<uint2*>(sm + SM_SC) + mb * 8 + g;
#pragma unroll 1
        for (int j = par; j < 16; j += 2) {
            const int i = 10 + j;
            const uint32_t ta = sb + i * TILE + offN;
            mbar_wait(bar_full + 8 * i);
            uint32_t a[4][4];
#pragma unroll
            for (int kb = 0; kb < 4; kb++) ldsm4(a[kb], ta ^ (kb << 5));
            float c0[4] = {0.f, 0.f, 0.f, 0.f}, c1[4] = {0.f, 0.f, 0.f, 0.f};
            mma16816(c0, a[0], bv[0], bv[1]); mma16816(c1, a[1], bv[2], bv[3]);
            mma16816(c0, a[2], bv[4], bv[5]); mma16816(c1, a[3], bv[6], bv[7]);
            const uint32_t lo = enc(c0[0] + c1[0]), hi = enc(c0[2] + c1[2]);
            if (t == 0) sdst[j * 32] = make_uint2(lo, hi);
            else if (t < 3) st_relaxed2(dst + j * 64, lo, hi);
            if (lane == 0 && (j == 4 + par || j == 14 + par)) mbar_arrive(bar_empty + (j < 6 ? 8 : 16));
        }
    }
    named_bar(1, 256);
    {
        const float4 own = reinterpret_cast<const float4*>(sm + SM_SC)[tid];
        uint32_t* ma = g_s + ((size_t)b * 3 + (r == 0 ? 1 : 0)) * WIN + tid * 4;
        uint32_t* mc = g_s + ((size_t)b * 3 + (r == 2 ? 1 : 2)) * WIN + tid * 4;
        uint4 pa = make_uint4(0u, 0u, 0u, 0u), pc = pa;
        uint32_t n = 0, pend = 3u;
        while (pend && ++n < SPIN_LIMIT) {
            ld_relaxed4_if(pa, ma, pend & 1u); ld_relaxed4_if(pc, mc, pend & 2u);
            pend = (full4(pa) ? 0u : 1u) | (full4(pc) ? 0u : 2u);
        }
        float s[4];
        const float o4[4] = {own.x, own.y, own.z, own.w};
        const float a4[4] = {__uint_as_float(pa.x), __uint_as_float(pa.y), __uint_as_float(pa.z), __uint_as_float(pa.w)};
        const float c4[4] = {__uint_as_float(pc.x), __uint_as_float(pc.y), __uint_as_float(pc.z), __uint_as_float(pc.w)};
        float m = -INFINITY;
#pragma unroll
        for (int k = 0; k < 4; k++) {
            const float first = r == 2 ? a4[k] + c4[k] : a4[k] + o4[k];
            const float last = r == 2 ? o4[k] : c4[k];
            s[k] = rbf(rbf(first + last) * 0.07216878364870322f);
            m = fmaxf(m, s[k]);
        }
#pragma unroll
        for (int o = 16; o; o >>= 1) m = fmaxf(m, __shfl_xor_sync(0xffffffffu, m, o));
        if (lane == 0) s_red[warp] = m;
        named_bar(1, 256);
        {
            const float4 m0 = *reinterpret_cast<const float4*>(s_red), m1 = *reinterpret_cast<const float4*>(s_red + 4);
            m = fmaxf(fmaxf(fmaxf(m0.x, m0.y), fmaxf(m0.z, m0.w)), fmaxf(fmaxf(m1.x, m1.y), fmaxf(m1.z, m1.w)));
        }
        float l = 0.f;
#pragma unroll
        for (int k = 0; k < 4; k++) { s[k] = __expf(s[k] - m); l += s[k]; }
#pragma unroll
        for (int o = 16; o; o >>= 1) l += __shfl_xor_sync(0xffffffffu, l, o);
        if (lane == 0) s_red[8 + warp] = l;
        named_bar(1, 256);
        {
            const float4 l0 = *reinterpret_cast<const float4*>(s_red + 8), l1 = *reinterpret_cast<const float4*>(s_red + 12);
            l = ((l0.x + l0.y) + (l0.z + l0.w)) + ((l1.x + l1.y) + (l1.z + l1.w));
        }
        const float inv = 1.f / l;
        reinterpret_cast<uint2*>(sm + SM_P)[tid] = make_uint2(pack_bf(s[0] * inv, s[2] * inv), pack_bf(s[1] * inv, s[3] * inv));
        named_bar(1, 256);
        st_relaxed4(ma, 0u, 0u, 0u, 0u);
        st_relaxed4(mc, 0u, 0u, 0u, 0u);
    }
    {
        float c0[4] = {0.f, 0.f, 0.f, 0.f}, c1[4] = {0.f, 0.f, 0.f, 0.f};
        const uint32_t pfrag = sb + SM_P + t * 8;
#pragma unroll 1
        for (int j = par; j < 16; j += 2) {
            uint2 bp[4];
#pragma unroll
            for (int kb = 0; kb < 4; kb++) bp[kb] = lds64(pfrag + j * 128 + kb * 32);
            mbar_wait(bar_full + 8 * j, j >= KC);
            uint32_t a[4][4];
#pragma unroll
            for (int kb = 0; kb < 4; kb++) ldsm4t(a[kb], sb + j * TILE + offT + kb * 2048);
            mma16816(c0, a[0], bp[0].x, bp[0].y); mma16816(c1, a[1], bp[1].x, bp[1].y);
            mma16816(c0, a[2], bp[2].x, bp[2].y); mma16816(c1, a[3], bp[3].x, bp[3].y);
        }
        if (t == 0) { s_part[par * 64 + mb * 16 + g] = c0[0] + c1[0]; s_part[par * 64 + mb * 16 + g + 8] = c0[2] + c1[2]; }
        named_bar(1, 256);
#pragma unroll
        for (int j = 0; j < 8; j++) {
            const int c = j * 8 + 2 * t;
            const float2 u0 = *reinterpret_cast<const float2*>(s_part + c), u1 = *reinterpret_cast<const float2*>(s_part + 64 + c);
            bv[j] = pack_bf(u0.x + u1.x, u0.y + u1.y);
        }
    }
    out_tiles(42, par, mb, sb, offT, bv, bar_full, lane, b);
}

}

namespace simple {

__device__ float g_q[NH * DH], g_o[NH * DH], g_h[DF];

__device__ __forceinline__ float col_dot(const float* __restrict__ v, const __nv_bfloat16* __restrict__ w, int n, int pitch) {
    float s = 0.f;
    for (int k = 0; k < n; k++) s = fmaf(v[k], __bfloat162float(w[(size_t)k * pitch]), s);
    return s;
}

__global__ void proj_kernel(const __nv_bfloat16* __restrict__ x, const __nv_bfloat16* __restrict__ wq, const __nv_bfloat16* __restrict__ wg,
                            const __nv_bfloat16* __restrict__ wu) {
    __shared__ float sx[D_MODEL];
    for (int i = threadIdx.x; i < D_MODEL; i += blockDim.x) sx[i] = __bfloat162float(x[i]);
    __syncthreads();
    const int c = blockIdx.x * blockDim.x + threadIdx.x;
    if (c < NH * DH) g_q[c] = rbf(col_dot(sx, wq + c, D_MODEL, NH * DH));
    else if (c < NH * DH + DF) {
        const int f = c - NH * DH;
        g_h[f] = rbf(rbf(gelu_tanh(rbf(col_dot(sx, wg + f, D_MODEL, DF)))) * rbf(col_dot(sx, wu + f, D_MODEL, DF)));
    }
}

__global__ void attn_kernel(const __nv_bfloat16* __restrict__ kc, const __nv_bfloat16* __restrict__ vc) {
    __shared__ float sq[DH], sp[WIN], sr[8];
    const int h = blockIdx.x, tid = threadIdx.x, lane = tid & 31, warp = tid >> 5;
    const size_t base = ((size_t)h * SK + (SK - WIN)) * DH;
    if (tid < DH) sq[tid] = g_q[h * DH + tid];
    __syncthreads();
    for (int k = warp; k < WIN; k += 8) {
        float s = 0.f;
        for (int d = lane; d < DH; d += 32) s = fmaf(sq[d], __bfloat162float(kc[base + (size_t)k * DH + d]), s);
        for (int o = 16; o; o >>= 1) s += __shfl_xor_sync(0xffffffffu, s, o);
        if (lane == 0) sp[k] = rbf(rbf(s) * 0.07216878364870322f);
    }
    __syncthreads();
    float m = -INFINITY;
    for (int k = tid; k < WIN; k += 256) m = fmaxf(m, sp[k]);
    for (int o = 16; o; o >>= 1) m = fmaxf(m, __shfl_xor_sync(0xffffffffu, m, o));
    if (lane == 0) sr[warp] = m;
    __syncthreads();
    for (int i = 0; i < 8; i++) m = fmaxf(m, sr[i]);
    __syncthreads();
    float l = 0.f;
    for (int k = tid; k < WIN; k += 256) { const float e = __expf(sp[k] - m); sp[k] = e; l += e; }
    for (int o = 16; o; o >>= 1) l += __shfl_xor_sync(0xffffffffu, l, o);
    if (lane == 0) sr[warp] = l;
    __syncthreads();
    l = 0.f;
    for (int i = 0; i < 8; i++) l += sr[i];
    const float inv = 1.f / l;
    for (int k = tid; k < WIN; k += 256) sp[k] = rbf(sp[k] * inv);
    __syncthreads();
    if (tid < DH) g_o[h * DH + tid] = rbf(col_dot(sp, vc + base + tid, WIN, DH));
}

__global__ void out_kernel(const __nv_bfloat16* __restrict__ x, const __nv_bfloat16* __restrict__ gate_w, const __nv_bfloat16* __restrict__ wo,
                           const __nv_bfloat16* __restrict__ wd, __nv_bfloat16* __restrict__ out) {
    __shared__ float sa[8][32], sf[8][32];
    const int lane = threadIdx.x & 31, warp = threadIdx.x >> 5, c = blockIdx.x * 32 + lane;
    sa[warp][lane] = col_dot(g_o + warp * (NH * DH / 8), wo + (size_t)warp * (NH * DH / 8) * D_MODEL + c, NH * DH / 8, D_MODEL);
    sf[warp][lane] = col_dot(g_h + warp * (DF / 8), wd + (size_t)warp * (DF / 8) * D_MODEL + c, DF / 8, D_MODEL);
    __syncthreads();
    if (warp) return;
    float s = 0.f, a = 0.f, f = 0.f;
    for (int i = lane; i < D_MODEL; i += 32) s += rbf(__bfloat162float(x[i]) * __bfloat162float(gate_w[i]));
    for (int o = 16; o; o >>= 1) s += __shfl_xor_sync(0xffffffffu, s, o);
    for (int i = 0; i < 8; i++) { a += sa[i][lane]; f += sf[i][lane]; }
    const float ga = rbf(1.f / (1.f + __expf(-rbf(s)))), gf = rbf(1.f - ga);
    out[c] = __float2bfloat16_rn(rbf(ga * rbf(a)) + rbf(gf * rbf(f)));
}

}

typedef CUresult (*EncodeFn)(CUtensorMap*, CUtensorMapDataType, cuuint32_t, void*, const cuuint64_t*, const cuuint64_t*, const cuuint32_t*,
                             const cuuint32_t*, CUtensorMapInterleave, CUtensorMapSwizzle, CUtensorMapL2promotion, CUtensorMapFloatOOBfill);

}

extern "C" void kernel_launch(void* const* d_in, const int* in_sizes, int n_in, void* d_out, int out_size) {
    static EncodeFn encode = nullptr;
    static int mode = 0;
    cudaLaunchConfig_t cfg = {};
    cfg.gridDim = dim3(NCTA); cfg.blockDim = dim3(NTHR); cfg.dynamicSmemBytes = SM_TOTAL; cfg.stream = cudaStreamPerThread;
    cudaLaunchAttribute at[1];
    at[0].id = cudaLaunchAttributeClusterDimension; at[0].val.clusterDim.x = CS; at[0].val.clusterDim.y = 1; at[0].val.clusterDim.z = 1;
    cfg.attrs = at; cfg.numAttrs = 1;
    if (!encode) {
        void* fn = nullptr;
        cudaDriverEntryPointQueryResult st;
        cudaGetDriverEntryPoint("cuTensorMapEncodeTiled", &fn, cudaEnableDefault, &st);
        encode = (EncodeFn)fn;
        cudaFuncSetAttribute(fused_decode_kernel, cudaFuncAttributeMaxDynamicSharedMemorySize, SM_TOTAL);
        cudaFuncSetAttribute(plain::plain_decode_kernel, cudaFuncAttributeMaxDynamicSharedMemorySize, plain::SM_TOTAL);
        int ncl = 0, dev = 0, nsm = 0, occ = 0;
        if (cudaOccupancyMaxActiveClusters(&ncl, fused_decode_kernel, &cfg) != cudaSuccess) ncl = 0;
        cudaGetDevice(&dev);
        cudaDeviceGetAttribute(&nsm, cudaDevAttrMultiProcessorCount, dev);
        cudaOccupancyMaxActiveBlocksPerMultiprocessor(&occ, plain::plain_decode_kernel, NTHR, plain::SM_TOTAL);
        mode = ncl >= NCL ? 0 : (nsm * occ >= plain::NCTA ? 1 : 2);
        (void)cudaGetLastError();
    }
    const __nv_bfloat16* in[10];
    for (int i = 0; i < 10; i++) in[i] = (const __nv_bfloat16*)d_in[i];
    __nv_bfloat16* out = (__nv_bfloat16*)d_out;
    if (mode == 2) {
        simple::proj_kernel<<<(NH * DH + DF) / 64, 64, 0, cudaStreamPerThread>>>(in[0], in[3], in[6], in[7]);
        simple::attn_kernel<<<NH, 256, 0, cudaStreamPerThread>>>(in[1], in[2]);
        simple::out_kernel<<<D_MODEL / 32, 256, 0, cudaStreamPerThread>>>(in[0], in[9], in[4], in[8], out);
        return;
    }
    Maps maps;
    const int src[7] = {3, 1, 2, 4, 6, 7, 8};
    const cuuint64_t cols[7] = {NH * DH, DH, DH, D_MODEL, DF, DF, D_MODEL};
    const cuuint64_t rows[7] = {D_MODEL, (cuuint64_t)NH * SK, (cuuint64_t)NH * SK, NH * DH, D_MODEL, D_MODEL, DF};
    for (int i = 0; i < 7; i++) {
        const cuuint64_t dim[2] = {cols[i], rows[i]};
        const cuuint64_t stride[1] = {cols[i] * 2};
        const cuuint32_t box[2] = {64, 64}, es[2] = {1, 1};
        encode(&maps.m[i], CU_TENSOR_MAP_DATA_TYPE_BFLOAT16, 2, d_in[src[i]], dim, stride, box, es, CU_TENSOR_MAP_INTERLEAVE_NONE,
               CU_TENSOR_MAP_SWIZZLE_128B, CU_TENSOR_MAP_L2_PROMOTION_NONE, CU_TENSOR_MAP_FLOAT_OOB_FILL_NONE);
    }
    if (mode == 1) plain::plain_decode_kernel<<<plain::NCTA, NTHR, plain::SM_TOTAL, cudaStreamPerThread>>>(in[3], in[6], in[0], in[9], out, maps);
    else cudaLaunchKernelEx(&cfg, fused_decode_kernel, in[3], in[6], in[0], in[9], out, maps);
}
```
